```python
import torch

def _softmax(x, axis=-1):
    return torch.softmax(x, dim=axis)

def _gelu(x):
    return torch.nn.functional.gelu(x, approximate='tanh')

def _silu(x):
    return torch.nn.functional.silu(x)

def _sigmoid(x):
    return torch.sigmoid(x)

def _layernorm(x, axis=-1, eps=1e-05):
    m = x.mean(dim=axis, keepdim=True)
    v = x.var(dim=axis, keepdim=True, unbiased=False)
    return (x - m) / torch.sqrt(v + eps)

def _scatter_add(tgt, idx, src, axis=0):
    return tgt.clone().index_add_(axis, idx, src)

def _segment_sum(src, seg, n):
    out = torch.zeros((n,) + src.shape[1:], dtype=src.dtype)
    return out.index_add_(0, seg, src)

def _pad(x, pw):
    flat = tuple((v for pair in reversed(pw) for v in pair))
    return torch.nn.functional.pad(x, flat)
kernel_name = 'standalone__conformer_family_branchformer__speech'

def setup_inputs():

    _w = lambda a: (lambda t: t.to(torch.bfloat16) if t.is_floating_point() else t)(torch.as_tensor(a))
    B, T, D, K = (2, 4000, 512, 3)
    s = float(D) ** (-0.5)
    return {'x': _w((lambda *s: torch.randn(*s, dtype=torch.bfloat16) * 0.05)(B, T, D)), 'w_q': _w((lambda *s: torch.randn(*s, dtype=torch.bfloat16) * 1.6)(D, D) * s), 'w_k': _w((lambda *s: torch.randn(*s, dtype=torch.bfloat16) * 1.6)(D, D) * s), 'w_v': _w((lambda *s: torch.randn(*s, dtype=torch.bfloat16) * 0.4)(D, D) * s), 'w_ao': _w((lambda *s: torch.randn(*s, dtype=torch.bfloat16) * 0.4)(D, D) * s), 'w_up': _w((lambda *s: torch.randn(*s, dtype=torch.bfloat16) * 0.8)(D, 2 * D) * s), 'dw': _w((lambda *s: torch.randn(*s, dtype=torch.bfloat16) * 0.8)(K, D) * (1.0 / K)), 'w_dn': _w((lambda *s: torch.randn(*s, dtype=torch.bfloat16) * 0.4)(D, D) * s), 'w_merge': _w((lambda *s: torch.randn(*s, dtype=torch.bfloat16) * 0.4)(2 * D, D) * s)}

def reference(x, w_q, w_k, w_v, w_ao, w_up, dw, w_dn, w_merge):
    B, T, D = x.shape
    K = dw.shape[0]
    xa = _layernorm(x, axis=-1)
    q = torch.einsum('btd,de->bte', xa, w_q)
    k = torch.einsum('btd,de->bte', xa, w_k)
    v = torch.einsum('btd,de->bte', xa, w_v)
    logits = torch.einsum('btd,bsd->bts', q, k) * float(D) ** (-0.5)
    attn = _softmax(logits, axis=-1)
    ya = torch.einsum('bts,bsd->btd', attn, v)
    ya = torch.einsum('btd,de->bte', ya, w_ao)
    xc = _layernorm(x, axis=-1)
    h = _gelu(torch.einsum('btd,de->bte', xc, w_up))
    u = h[..., :D].clone()
    g = _layernorm(h[..., D:], axis=-1)
    pad = K // 2
    gp = _pad(g, ((0, 0), (pad, pad), (0, 0)))
    conv = torch.zeros_like(g)
    for i in range(K):
        conv = conv + gp[:, i:i + T, :] * dw[i][None, None, :]
    yc = torch.einsum('btd,de->bte', u * conv, w_dn)
    merged = torch.concatenate([ya, yc], axis=-1)
    out = torch.einsum('btf,fd->btd', merged, w_merge)
    return x + out
```

```cpp
#include <cuda_runtime.h>
#include <cuda_bf16.h>
#include <cuda.h>
#include <stdint.h>

namespace bf {

constexpr int TT = 4000, DD = 512, NTILE = 63;
constexpr uint32_t CH = 8192, SLOT = 32768, NS = 5, TILE = 65536;
constexpr uint32_t OFF_Q = NS * SLOT;
constexpr uint32_t OFF_P = OFF_Q + 7 * CH;
constexpr uint32_t OFF_EX = OFF_Q + TILE;
constexpr uint32_t OFF_BAR = OFF_EX + 2048;
constexpr uint32_t SMEM_BYTES = OFF_BAR + 256;
constexpr int NCTA = 132;
constexpr uint32_t N_ATT0 = 48, N_FIN0 = 48 + 2 * NTILE;

struct Maps { CUtensorMap up, q, k, v, ao, dn, mg; };

__device__ __align__(1024) uint8_t g_xa[2 * NTILE * TILE];
__device__ __align__(1024) uint8_t g_uc[128 * TILE];
__device__ __align__(1024) uint8_t g_wqk[8 * TILE];
__device__ __align__(1024) uint8_t g_wf[16 * TILE];
__device__ __align__(1024) uint4 g_halo[64 * 2 * 8 * 2 * 32];
__device__ uint32_t g_flags[64 * 32];
constexpr int F_WQK = 0, F_XA = 16, F_WF = 18, F_DONE = 19;

__device__ __forceinline__ uint32_t smem_u32(const void* p) { return (uint32_t)__cvta_generic_to_shared(p); }
__device__ __forceinline__ void mbar_init(uint32_t bar, uint32_t cnt) { asm volatile("mbarrier.init.shared::cta.b64 [%0], %1;" :: "r"(bar), "r"(cnt)); }
__device__ __forceinline__ void mbar_expect_tx(uint32_t bar, uint32_t bytes) { asm volatile("mbarrier.arrive.expect_tx.shared::cta.b64 _, [%0], %1;" :: "r"(bar), "r"(bytes) : "memory"); }
__device__ __forceinline__ void mbar_arrive(uint32_t bar) { asm volatile("mbarrier.arrive.shared::cta.b64 _, [%0];" :: "r"(bar) : "memory"); }
__device__ __forceinline__ void mbar_arrive_cluster(uint32_t a) { asm volatile("mbarrier.arrive.shared::cluster.b64 _, [%0];" :: "r"(a) : "memory"); }
__device__ __forceinline__ void mbar_arrive_cluster_rel(uint32_t a) { asm volatile("mbarrier.arrive.release.cluster.shared::cluster.b64 _, [%0];" :: "r"(a) : "memory"); }
__device__ __forceinline__ bool mbar_try_wait(uint32_t bar, uint32_t parity) {
  uint32_t ok;
  asm volatile("{\n.reg .pred p;\nmbarrier.try_wait.parity.shared::cta.b64 p, [%1], %2;\nselp.b32 %0, 1, 0, p;\n}\n" : "=r"(ok) : "r"(bar), "r"(parity) : "memory");
  return ok;
}
__device__ __forceinline__ bool mbar_try_wait_cl(uint32_t bar, uint32_t parity) {
  uint32_t ok;
  asm volatile("{\n.reg .pred p;\nmbarrier.try_wait.parity.acquire.cluster.shared::cta.b64 p, [%1], %2;\nselp.b32 %0, 1, 0, p;\n}\n" : "=r"(ok) : "r"(bar), "r"(parity) : "memory");
  return ok;
}
#define TRAP(a, b) __trap()
#define MARK(c)
constexpr uint32_t TIMEOUT_CLK = 1u << 30;
__device__ __forceinline__ uint32_t clk32() { uint32_t r; asm volatile("mov.u32 %0, %%clock;" : "=r"(r)); return r; }
__device__ __forceinline__ void mbar_wait(uint32_t bar, uint32_t parity) {
  if (mbar_try_wait(bar, parity)) return;
  const uint32_t t0 = clk32();
  while (!mbar_try_wait(bar, parity)) { if (clk32() - t0 > TIMEOUT_CLK) TRAP(bar, parity); }
}
__device__ __forceinline__ void mbar_wait_cl(uint32_t bar, uint32_t parity) {
  const uint32_t t0 = clk32();
  while (!mbar_try_wait_cl(bar, parity)) { if (clk32() - t0 > TIMEOUT_CLK) TRAP(bar, parity); }
}
__device__ __forceinline__ uint32_t mapa(uint32_t addr, uint32_t rank) { uint32_t r; asm volatile("mapa.shared::cluster.u32 %0, %1, %2;" : "=r"(r) : "r"(addr), "r"(rank)); return r; }
__device__ __forceinline__ void bulk_g2s(uint32_t dst, const void* src, uint32_t bytes, uint32_t bar) {
  asm volatile("cp.async.bulk.shared::cluster.global.mbarrier::complete_tx::bytes [%0], [%1], %2, [%3];" :: "r"(dst), "l"(src), "r"(bytes), "r"(bar) : "memory");
}
__device__ __forceinline__ void bulk_g2s_mc(uint32_t dst, const void* src, uint32_t bytes, uint32_t bar) {
  asm volatile("cp.async.bulk.shared::cluster.global.mbarrier::complete_tx::bytes.multicast::cluster [%0], [%1], %2, [%3], %4;" :: "r"(dst), "l"(src), "r"(bytes), "r"(bar), "h"((uint16_t)3) : "memory");
}
__device__ __forceinline__ void tma3d(uint32_t dst, const CUtensorMap* m, int c1, int c2, uint32_t bar) {
  asm volatile("cp.async.bulk.tensor.3d.shared::cluster.global.mbarrier::complete_tx::bytes [%0], [%1, {%3, %4, %5}], [%2];"
               :: "r"(dst), "l"(m), "r"(bar), "r"(0), "r"(c1), "r"(c2) : "memory");
}
__device__ __forceinline__ void tma3d_mc(uint32_t dst, const CUtensorMap* m, int c1, int c2, uint32_t bar) {
  asm volatile("cp.async.bulk.tensor.3d.shared::cluster.global.mbarrier::complete_tx::bytes.multicast::cluster [%0], [%1, {%3, %4, %5}], [%2], %6;"
               :: "r"(dst), "l"(m), "r"(bar), "r"(0), "r"(c1), "r"(c2), "h"((uint16_t)3) : "memory");
}
__device__ __forceinline__ void wg_fence() { asm volatile("wgmma.fence.sync.aligned;" ::: "memory"); }
__device__ __forceinline__ void wg_commit() { asm volatile("wgmma.commit_group.sync.aligned;" ::: "memory"); }
template <int N> __device__ __forceinline__ void wg_wait() { asm volatile("wgmma.wait_group.sync.aligned %0;" :: "n"(N) : "memory"); }
__device__ __forceinline__ void cluster_arrive() { asm volatile("barrier.cluster.arrive.aligned;" ::: "memory"); }
__device__ __forceinline__ void cluster_wait() { asm volatile("barrier.cluster.wait.aligned;" ::: "memory"); }
__device__ __forceinline__ uint32_t cluster_rank() { uint32_t r; asm volatile("mov.u32 %0, %%cluster_ctarank;" : "=r"(r)); return r; }
__device__ __forceinline__ void bar_sync(int id) { asm volatile("bar.sync %0, 256;" :: "r"(id) : "memory"); }
__device__ __forceinline__ void bar_arrive(int id) { asm volatile("bar.arrive %0, 256;" :: "r"(id) : "memory"); }
__device__ __forceinline__ void fence_async_smem() { asm volatile("fence.proxy.async.shared::cta;" ::: "memory"); }
__device__ __forceinline__ void fence_async_all() { asm volatile("fence.proxy.async;" ::: "memory"); }
__device__ __forceinline__ uint64_t desc_k(uint32_t addr) { return (uint64_t)((addr & 0x3FFFF) >> 4) | ((uint64_t)1 << 16) | ((uint64_t)64 << 32) | ((uint64_t)1 << 62); }
__device__ __forceinline__ uint64_t desc_mn(uint32_t addr) { return (uint64_t)((addr & 0x3FFFF) >> 4) | ((uint64_t)(CH >> 4) << 16) | ((uint64_t)64 << 32) | ((uint64_t)1 << 62); }
template <int R> __device__ __forceinline__ void reg_alloc() { asm volatile("setmaxnreg.inc.sync.aligned.u32 %0;" :: "n"(R)); }
template <int R> __device__ __forceinline__ void reg_dealloc() { asm volatile("setmaxnreg.dec.sync.aligned.u32 %0;" :: "n"(R)); }
template <int N> __device__ __forceinline__ void fence_regs(float (&r)[N]) {
#pragma unroll
  for (int i = 0; i < N; i++) asm volatile("" : "+f"(r[i]) :: "memory");
}
template <int N> __device__ __forceinline__ void fence_regs(uint32_t (&r)[N]) {
#pragma unroll
  for (int i = 0; i < N; i++) asm volatile("" : "+r"(r[i]) :: "memory");
}
__device__ __forceinline__ uint32_t pack2(float lo, float hi) { uint32_t r; asm("cvt.rn.bf16x2.f32 %0, %1, %2;" : "=r"(r) : "f"(hi), "f"(lo)); return r; }
__device__ __forceinline__ float blo(uint32_t v) { return __uint_as_float(v << 16); }
__device__ __forceinline__ float bhi(uint32_t v) { return __uint_as_float(v & 0xFFFF0000u); }
__device__ __forceinline__ float ex2(float x) { float r; asm("ex2.approx.ftz.f32 %0, %1;" : "=f"(r) : "f"(x)); return r; }
__device__ __forceinline__ float gelu(float x) {
  float z = x * fmaf(x * x, 0.044715f * 0.7978845608028654f, 0.7978845608028654f), t;
  asm("tanh.approx.f32 %0, %1;" : "=f"(t) : "f"(z));
  float h = 0.5f * x;
  return fmaf(h, t, h);
}
__device__ __forceinline__ uint32_t hfma2(uint32_t a, uint32_t b, uint32_t c) { uint32_t r; asm("fma.rn.bf16x2 %0, %1, %2, %3;" : "=r"(r) : "r"(a), "r"(b), "r"(c)); return r; }
__device__ __forceinline__ uint32_t hmul2(uint32_t a, uint32_t b) { uint32_t r; asm("mul.rn.bf16x2 %0, %1, %2;" : "=r"(r) : "r"(a), "r"(b)); return r; }
__device__ __forceinline__ void stsm4(uint32_t addr, uint32_t a, uint32_t b, uint32_t c, uint32_t d) {
  asm volatile("stmatrix.sync.aligned.m8n8.x4.shared.b16 [%0], {%1, %2, %3, %4};" :: "r"(addr), "r"(a), "r"(b), "r"(c), "r"(d) : "memory");
}
__device__ __forceinline__ void ldsm4(uint32_t addr, uint32_t& a, uint32_t& b, uint32_t& c, uint32_t& d) {
  asm volatile("ldmatrix.sync.aligned.m8n8.x4.shared.b16 {%0, %1, %2, %3}, [%4];" : "=r"(a), "=r"(b), "=r"(c), "=r"(d) : "r"(addr) : "memory");
}
__device__ __forceinline__ void sts128(uint32_t addr, uint32_t a, uint32_t b, uint32_t c, uint32_t d) {
  asm volatile("st.shared.v4.b32 [%0], {%1, %2, %3, %4};" :: "r"(addr), "r"(a), "r"(b), "r"(c), "r"(d) : "memory");
}
__device__ __forceinline__ uint32_t ld_acquire(const uint32_t* p) { uint32_t v; asm volatile("ld.acquire.gpu.global.u32 %0, [%1];" : "=r"(v) : "l"(p) : "memory"); return v; }
__device__ __forceinline__ void wait_flag(int idx, uint32_t target) {
  const uint32_t t0 = clk32();
  while ((int)(ld_acquire(&g_flags[idx * 32]) - target) < 0) { __nanosleep(40); if (clk32() - t0 > TIMEOUT_CLK) TRAP(idx, target); }
  fence_async_all();
}
__device__ __forceinline__ void signal_flag(int idx) {
  fence_async_all();
  __threadfence();
  __syncwarp();
  if ((threadIdx.x & 31) == 0) atomicAdd(&g_flags[idx * 32], 1u);
}

__device__ __forceinline__ void wgmma_ss_n256_tb1(float (&d)[128], uint64_t da, uint64_t db, int scale_d) {
  asm volatile("{\n.reg .pred p;\nsetp.ne.b32 p, %130, 0;\n"
    "wgmma.mma_async.sync.aligned.m64n256k16.f32.bf16.bf16 {%0, %1, %2, %3, %4, %5, %6, %7, %8, %9, %10, %11, %12, %13, %14, %15, %16, %17, %18, %19, %20, %21, %22, %23, %24, %25, %26, %27, %28, %29, %30, %31, %32, %33, %34, %35, %36, %37, %38, %39, %40, %41, %42, %43, %44, %45, %46, %47, %48, %49, %50, %51, %52, %53, %54, %55, %56, %57, %58, %59, %60, %61, %62, %63, %64, %65, %66, %67, %68, %69, %70, %71, %72, %73, %74, %75, %76, %77, %78, %79, %80, %81, %82, %83, %84, %85, %86, %87, %88, %89, %90, %91, %92, %93, %94, %95, %96, %97, %98, %99, %100, %101, %102, %103, %104, %105, %106, %107, %108, %109, %110, %111, %112, %113, %114, %115, %116, %117, %118, %119, %120, %121, %122, %123, %124, %125, %126, %127}, %128, %129, p, 1, 1, 0, 1;\n}\n"
    : "+f"(d[0]), "+f"(d[1]), "+f"(d[2]), "+f"(d[3]), "+f"(d[4]), "+f"(d[5]), "+f"(d[6]), "+f"(d[7]), "+f"(d[8]), "+f"(d[9]), "+f"(d[10]), "+f"(d[11]), "+f"(d[12]), "+f"(d[13]), "+f"(d[14]), "+f"(d[15]), "+f"(d[16]), "+f"(d[17]), "+f"(d[18]), "+f"(d[19]), "+f"(d[20]), "+f"(d[21]), "+f"(d[22]), "+f"(d[23]), "+f"(d[24]), "+f"(d[25]), "+f"(d[26]), "+f"(d[27]), "+f"(d[28]), "+f"(d[29]), "+f"(d[30]), "+f"(d[31]), "+f"(d[32]), "+f"(d[33]), "+f"(d[34]), "+f"(d[35]), "+f"(d[36]), "+f"(d[37]), "+f"(d[38]), "+f"(d[39]), "+f"(d[40]), "+f"(d[41]), "+f"(d[42]), "+f"(d[43]), "+f"(d[44]), "+f"(d[45]), "+f"(d[46]), "+f"(d[47]), "+f"(d[48]), "+f"(d[49]), "+f"(d[50]), "+f"(d[51]), "+f"(d[52]), "+f"(d[53]), "+f"(d[54]), "+f"(d[55]), "+f"(d[56]), "+f"(d[57]), "+f"(d[58]), "+f"(d[59]), "+f"(d[60]), "+f"(d[61]), "+f"(d[62]), "+f"(d[63]), "+f"(d[64]), "+f"(d[65]), "+f"(d[66]), "+f"(d[67]), "+f"(d[68]), "+f"(d[69]), "+f"(d[70]), "+f"(d[71]), "+f"(d[72]), "+f"(d[73]), "+f"(d[74]), "+f"(d[75]), "+f"(d[76]), "+f"(d[77]), "+f"(d[78]), "+f"(d[79]), "+f"(d[80]), "+f"(d[81]), "+f"(d[82]), "+f"(d[83]), "+f"(d[84]), "+f"(d[85]), "+f"(d[86]), "+f"(d[87]), "+f"(d[88]), "+f"(d[89]), "+f"(d[90]), "+f"(d[91]), "+f"(d[92]), "+f"(d[93]), "+f"(d[94]), "+f"(d[95]), "+f"(d[96]), "+f"(d[97]), "+f"(d[98]), "+f"(d[99]), "+f"(d[100]), "+f"(d[101]), "+f"(d[102]), "+f"(d[103]), "+f"(d[104]), "+f"(d[105]), "+f"(d[106]), "+f"(d[107]), "+f"(d[108]), "+f"(d[109]), "+f"(d[110]), "+f"(d[111]), "+f"(d[112]), "+f"(d[113]), "+f"(d[114]), "+f"(d[115]), "+f"(d[116]), "+f"(d[117]), "+f"(d[118]), "+f"(d[119]), "+f"(d[120]), "+f"(d[121]), "+f"(d[122]), "+f"(d[123]), "+f"(d[124]), "+f"(d[125]), "+f"(d[126]), "+f"(d[127])
    : "l"(da), "l"(db), "r"(scale_d));
}

__device__ __forceinline__ void wgmma_ss_n256_tb0(float (&d)[128], uint64_t da, uint64_t db, int scale_d) {
  asm volatile("{\n.reg .pred p;\nsetp.ne.b32 p, %130, 0;\n"
    "wgmma.mma_async.sync.aligned.m64n256k16.f32.bf16.bf16 {%0, %1, %2, %3, %4, %5, %6, %7, %8, %9, %10, %11, %12, %13, %14, %15, %16, %17, %18, %19, %20, %21, %22, %23, %24, %25, %26, %27, %28, %29, %30, %31, %32, %33, %34, %35, %36, %37, %38, %39, %40, %41, %42, %43, %44, %45, %46, %47, %48, %49, %50, %51, %52, %53, %54, %55, %56, %57, %58, %59, %60, %61, %62, %63, %64, %65, %66, %67, %68, %69, %70, %71, %72, %73, %74, %75, %76, %77, %78, %79, %80, %81, %82, %83, %84, %85, %86, %87, %88, %89, %90, %91, %92, %93, %94, %95, %96, %97, %98, %99, %100, %101, %102, %103, %104, %105, %106, %107, %108, %109, %110, %111, %112, %113, %114, %115, %116, %117, %118, %119, %120, %121, %122, %123, %124, %125, %126, %127}, %128, %129, p, 1, 1, 0, 0;\n}\n"
    : "+f"(d[0]), "+f"(d[1]), "+f"(d[2]), "+f"(d[3]), "+f"(d[4]), "+f"(d[5]), "+f"(d[6]), "+f"(d[7]), "+f"(d[8]), "+f"(d[9]), "+f"(d[10]), "+f"(d[11]), "+f"(d[12]), "+f"(d[13]), "+f"(d[14]), "+f"(d[15]), "+f"(d[16]), "+f"(d[17]), "+f"(d[18]), "+f"(d[19]), "+f"(d[20]), "+f"(d[21]), "+f"(d[22]), "+f"(d[23]), "+f"(d[24]), "+f"(d[25]), "+f"(d[26]), "+f"(d[27]), "+f"(d[28]), "+f"(d[29]), "+f"(d[30]), "+f"(d[31]), "+f"(d[32]), "+f"(d[33]), "+f"(d[34]), "+f"(d[35]), "+f"(d[36]), "+f"(d[37]), "+f"(d[38]), "+f"(d[39]), "+f"(d[40]), "+f"(d[41]), "+f"(d[42]), "+f"(d[43]), "+f"(d[44]), "+f"(d[45]), "+f"(d[46]), "+f"(d[47]), "+f"(d[48]), "+f"(d[49]), "+f"(d[50]), "+f"(d[51]), "+f"(d[52]), "+f"(d[53]), "+f"(d[54]), "+f"(d[55]), "+f"(d[56]), "+f"(d[57]), "+f"(d[58]), "+f"(d[59]), "+f"(d[60]), "+f"(d[61]), "+f"(d[62]), "+f"(d[63]), "+f"(d[64]), "+f"(d[65]), "+f"(d[66]), "+f"(d[67]), "+f"(d[68]), "+f"(d[69]), "+f"(d[70]), "+f"(d[71]), "+f"(d[72]), "+f"(d[73]), "+f"(d[74]), "+f"(d[75]), "+f"(d[76]), "+f"(d[77]), "+f"(d[78]), "+f"(d[79]), "+f"(d[80]), "+f"(d[81]), "+f"(d[82]), "+f"(d[83]), "+f"(d[84]), "+f"(d[85]), "+f"(d[86]), "+f"(d[87]), "+f"(d[88]), "+f"(d[89]), "+f"(d[90]), "+f"(d[91]), "+f"(d[92]), "+f"(d[93]), "+f"(d[94]), "+f"(d[95]), "+f"(d[96]), "+f"(d[97]), "+f"(d[98]), "+f"(d[99]), "+f"(d[100]), "+f"(d[101]), "+f"(d[102]), "+f"(d[103]), "+f"(d[104]), "+f"(d[105]), "+f"(d[106]), "+f"(d[107]), "+f"(d[108]), "+f"(d[109]), "+f"(d[110]), "+f"(d[111]), "+f"(d[112]), "+f"(d[113]), "+f"(d[114]), "+f"(d[115]), "+f"(d[116]), "+f"(d[117]), "+f"(d[118]), "+f"(d[119]), "+f"(d[120]), "+f"(d[121]), "+f"(d[122]), "+f"(d[123]), "+f"(d[124]), "+f"(d[125]), "+f"(d[126]), "+f"(d[127])
    : "l"(da), "l"(db), "r"(scale_d));
}

__device__ __forceinline__ void wgmma_rs_n256_tb1(float (&d)[128], uint32_t a0, uint32_t a1, uint32_t a2, uint32_t a3, uint64_t db, int scale_d) {
  asm volatile("{\n.reg .pred p;\nsetp.ne.b32 p, %133, 0;\n"
    "wgmma.mma_async.sync.aligned.m64n256k16.f32.bf16.bf16 {%0, %1, %2, %3, %4, %5, %6, %7, %8, %9, %10, %11, %12, %13, %14, %15, %16, %17, %18, %19, %20, %21, %22, %23, %24, %25, %26, %27, %28, %29, %30, %31, %32, %33, %34, %35, %36, %37, %38, %39, %40, %41, %42, %43, %44, %45, %46, %47, %48, %49, %50, %51, %52, %53, %54, %55, %56, %57, %58, %59, %60, %61, %62, %63, %64, %65, %66, %67, %68, %69, %70, %71, %72, %73, %74, %75, %76, %77, %78, %79, %80, %81, %82, %83, %84, %85, %86, %87, %88, %89, %90, %91, %92, %93, %94, %95, %96, %97, %98, %99, %100, %101, %102, %103, %104, %105, %106, %107, %108, %109, %110, %111, %112, %113, %114, %115, %116, %117, %118, %119, %120, %121, %122, %123, %124, %125, %126, %127}, {%128, %129, %130, %131}, %132, p, 1, 1, 1;\n}\n"
    : "+f"(d[0]), "+f"(d[1]), "+f"(d[2]), "+f"(d[3]), "+f"(d[4]), "+f"(d[5]), "+f"(d[6]), "+f"(d[7]), "+f"(d[8]), "+f"(d[9]), "+f"(d[10]), "+f"(d[11]), "+f"(d[12]), "+f"(d[13]), "+f"(d[14]), "+f"(d[15]), "+f"(d[16]), "+f"(d[17]), "+f"(d[18]), "+f"(d[19]), "+f"(d[20]), "+f"(d[21]), "+f"(d[22]), "+f"(d[23]), "+f"(d[24]), "+f"(d[25]), "+f"(d[26]), "+f"(d[27]), "+f"(d[28]), "+f"(d[29]), "+f"(d[30]), "+f"(d[31]), "+f"(d[32]), "+f"(d[33]), "+f"(d[34]), "+f"(d[35]), "+f"(d[36]), "+f"(d[37]), "+f"(d[38]), "+f"(d[39]), "+f"(d[40]), "+f"(d[41]), "+f"(d[42]), "+f"(d[43]), "+f"(d[44]), "+f"(d[45]), "+f"(d[46]), "+f"(d[47]), "+f"(d[48]), "+f"(d[49]), "+f"(d[50]), "+f"(d[51]), "+f"(d[52]), "+f"(d[53]), "+f"(d[54]), "+f"(d[55]), "+f"(d[56]), "+f"(d[57]), "+f"(d[58]), "+f"(d[59]), "+f"(d[60]), "+f"(d[61]), "+f"(d[62]), "+f"(d[63]), "+f"(d[64]), "+f"(d[65]), "+f"(d[66]), "+f"(d[67]), "+f"(d[68]), "+f"(d[69]), "+f"(d[70]), "+f"(d[71]), "+f"(d[72]), "+f"(d[73]), "+f"(d[74]), "+f"(d[75]), "+f"(d[76]), "+f"(d[77]), "+f"(d[78]), "+f"(d[79]), "+f"(d[80]), "+f"(d[81]), "+f"(d[82]), "+f"(d[83]), "+f"(d[84]), "+f"(d[85]), "+f"(d[86]), "+f"(d[87]), "+f"(d[88]), "+f"(d[89]), "+f"(d[90]), "+f"(d[91]), "+f"(d[92]), "+f"(d[93]), "+f"(d[94]), "+f"(d[95]), "+f"(d[96]), "+f"(d[97]), "+f"(d[98]), "+f"(d[99]), "+f"(d[100]), "+f"(d[101]), "+f"(d[102]), "+f"(d[103]), "+f"(d[104]), "+f"(d[105]), "+f"(d[106]), "+f"(d[107]), "+f"(d[108]), "+f"(d[109]), "+f"(d[110]), "+f"(d[111]), "+f"(d[112]), "+f"(d[113]), "+f"(d[114]), "+f"(d[115]), "+f"(d[116]), "+f"(d[117]), "+f"(d[118]), "+f"(d[119]), "+f"(d[120]), "+f"(d[121]), "+f"(d[122]), "+f"(d[123]), "+f"(d[124]), "+f"(d[125]), "+f"(d[126]), "+f"(d[127])
    : "r"(a0), "r"(a1), "r"(a2), "r"(a3), "l"(db), "r"(scale_d));
}

__device__ __forceinline__ void wgmma_ss_n64_tb0(float (&d)[32], uint64_t da, uint64_t db, int scale_d) {
  asm volatile("{\n.reg .pred p;\nsetp.ne.b32 p, %34, 0;\n"
    "wgmma.mma_async.sync.aligned.m64n64k16.f32.bf16.bf16 {%0, %1, %2, %3, %4, %5, %6, %7, %8, %9, %10, %11, %12, %13, %14, %15, %16, %17, %18, %19, %20, %21, %22, %23, %24, %25, %26, %27, %28, %29, %30, %31}, %32, %33, p, 1, 1, 0, 0;\n}\n"
    : "+f"(d[0]), "+f"(d[1]), "+f"(d[2]), "+f"(d[3]), "+f"(d[4]), "+f"(d[5]), "+f"(d[6]), "+f"(d[7]), "+f"(d[8]), "+f"(d[9]), "+f"(d[10]), "+f"(d[11]), "+f"(d[12]), "+f"(d[13]), "+f"(d[14]), "+f"(d[15]), "+f"(d[16]), "+f"(d[17]), "+f"(d[18]), "+f"(d[19]), "+f"(d[20]), "+f"(d[21]), "+f"(d[22]), "+f"(d[23]), "+f"(d[24]), "+f"(d[25]), "+f"(d[26]), "+f"(d[27]), "+f"(d[28]), "+f"(d[29]), "+f"(d[30]), "+f"(d[31])
    : "l"(da), "l"(db), "r"(scale_d));
}

__device__ __forceinline__ void wgmma_rs_n64_tb0(float (&d)[32], uint32_t a0, uint32_t a1, uint32_t a2, uint32_t a3, uint64_t db, int scale_d) {
  asm volatile("{\n.reg .pred p;\nsetp.ne.b32 p, %37, 0;\n"
    "wgmma.mma_async.sync.aligned.m64n64k16.f32.bf16.bf16 {%0, %1, %2, %3, %4, %5, %6, %7, %8, %9, %10, %11, %12, %13, %14, %15, %16, %17, %18, %19, %20, %21, %22, %23, %24, %25, %26, %27, %28, %29, %30, %31}, {%32, %33, %34, %35}, %36, p, 1, 1, 0;\n}\n"
    : "+f"(d[0]), "+f"(d[1]), "+f"(d[2]), "+f"(d[3]), "+f"(d[4]), "+f"(d[5]), "+f"(d[6]), "+f"(d[7]), "+f"(d[8]), "+f"(d[9]), "+f"(d[10]), "+f"(d[11]), "+f"(d[12]), "+f"(d[13]), "+f"(d[14]), "+f"(d[15]), "+f"(d[16]), "+f"(d[17]), "+f"(d[18]), "+f"(d[19]), "+f"(d[20]), "+f"(d[21]), "+f"(d[22]), "+f"(d[23]), "+f"(d[24]), "+f"(d[25]), "+f"(d[26]), "+f"(d[27]), "+f"(d[28]), "+f"(d[29]), "+f"(d[30]), "+f"(d[31])
    : "r"(a0), "r"(a1), "r"(a2), "r"(a3), "l"(db), "r"(scale_d));
}

__device__ __forceinline__ void wgmma_ss_n32_tb0(float (&d)[16], uint64_t da, uint64_t db, int scale_d) {
  asm volatile("{\n.reg .pred p;\nsetp.ne.b32 p, %18, 0;\n"
    "wgmma.mma_async.sync.aligned.m64n32k16.f32.bf16.bf16 {%0, %1, %2, %3, %4, %5, %6, %7, %8, %9, %10, %11, %12, %13, %14, %15}, %16, %17, p, 1, 1, 0, 0;\n}\n"
    : "+f"(d[0]), "+f"(d[1]), "+f"(d[2]), "+f"(d[3]), "+f"(d[4]), "+f"(d[5]), "+f"(d[6]), "+f"(d[7]), "+f"(d[8]), "+f"(d[9]), "+f"(d[10]), "+f"(d[11]), "+f"(d[12]), "+f"(d[13]), "+f"(d[14]), "+f"(d[15])
    : "l"(da), "l"(db), "r"(scale_d));
}

__device__ __forceinline__ void wgmma_rs_n32_tb0(float (&d)[16], uint32_t a0, uint32_t a1, uint32_t a2, uint32_t a3, uint64_t db, int scale_d) {
  asm volatile("{\n.reg .pred p;\nsetp.ne.b32 p, %21, 0;\n"
    "wgmma.mma_async.sync.aligned.m64n32k16.f32.bf16.bf16 {%0, %1, %2, %3, %4, %5, %6, %7, %8, %9, %10, %11, %12, %13, %14, %15}, {%16, %17, %18, %19}, %20, p, 1, 1, 0;\n}\n"
    : "+f"(d[0]), "+f"(d[1]), "+f"(d[2]), "+f"(d[3]), "+f"(d[4]), "+f"(d[5]), "+f"(d[6]), "+f"(d[7]), "+f"(d[8]), "+f"(d[9]), "+f"(d[10]), "+f"(d[11]), "+f"(d[12]), "+f"(d[13]), "+f"(d[14]), "+f"(d[15])
    : "r"(a0), "r"(a1), "r"(a2), "r"(a3), "l"(db), "r"(scale_d));
}

struct Ctx {
  uint32_t sb;
  uint32_t pdelta;
  uint32_t fb, ph;
  __device__ __forceinline__ uint32_t slot(uint32_t n) const { return sb + (n % NS) * SLOT; }
  __device__ __forceinline__ uint32_t full(uint32_t n, uint32_t w) const { return sb + OFF_BAR + 40 * w + 8 * (n % NS); }
  __device__ __forceinline__ uint32_t empty(uint32_t n) const { return sb + OFF_BAR + 80 + 8 * (n % NS); }
  __device__ __forceinline__ uint32_t afull(int h) const { return sb + OFF_BAR + 120 + 8 * h; }
  __device__ __forceinline__ uint32_t afree(int h) const { return sb + OFF_BAR + 136 + 8 * h; }
  __device__ __forceinline__ uint32_t gbar() const { return sb + OFF_BAR + 152; }
  __device__ __forceinline__ uint32_t dbar() const { return sb + OFF_BAR + 160; }
  __device__ __forceinline__ void wait_full(uint32_t n) {
    const uint32_t s = n % NS;
    mbar_wait(fb + 8 * s, (ph >> s) & 1);
    ph ^= 1u << s;
  }
  __device__ __forceinline__ void release(uint32_t n) const {
    if ((threadIdx.x & 31) == 0) { uint32_t e = empty(n); mbar_arrive(e); mbar_arrive_cluster(e + pdelta); }
  }
  __device__ __forceinline__ uint32_t acquire(uint32_t n, uint32_t w) const {
    MARK(10000 + n);
    if (n >= NS) mbar_wait(empty(n), ((n / NS) - 1) & 1);
    mbar_expect_tx(full(n, w), SLOT);
    return slot(n);
  }
};

template <int TB, class Pre, class Post>
__device__ __forceinline__ void gemm8(Ctx& cx, float (&acc)[128], uint32_t n0, uint32_t nstep, Pre pre, Post post) {
#pragma unroll 1
  for (int kb = 0; kb < 8; kb++) {
    uint32_t n = n0 + kb * nstep;
    pre(kb);
    cx.wait_full(n);
    uint64_t da = desc_k(cx.sb + OFF_Q + kb * CH);
    uint64_t db = TB ? desc_mn(cx.slot(n)) : desc_k(cx.slot(n));
    wg_fence();
#pragma unroll
    for (int k = 0; k < 4; k++) {
      if (TB) wgmma_ss_n256_tb1(acc, da + k * 2, db + k * 128, (kb | k) != 0);
      else wgmma_ss_n256_tb0(acc, da + k * 2, db + k * 2, (kb | k) != 0);
    }
    wg_commit();
    if (kb > 0) { wg_wait<1>(); cx.release(n - nstep); post(kb - 1); }
  }
  wg_wait<0>();
  fence_regs(acc);
  cx.release(n0 + 7 * nstep);
  post(7);
}

__device__ __forceinline__ int sigma(int r) { return (r & ~30) | ((r & 6) << 2) | ((r & 24) >> 2); }

__global__ void __cluster_dims__(2, 1, 1) __launch_bounds__(384, 1)
bf_kernel(const __grid_constant__ Maps maps, const __nv_bfloat16* __restrict__ x, const __nv_bfloat16* __restrict__ dw,
          __nv_bfloat16* __restrict__ out, int mode) {
  extern __shared__ __align__(1024) uint8_t smem_raw[];
  Ctx cx;
  cx.sb = smem_u32(smem_raw);
  const uint32_t sb = cx.sb;
  const int tid = threadIdx.x, lane = tid & 31, warp = __shfl_sync(~0u, tid >> 5, 0);
  const uint32_t rank = cluster_rank();
  cx.pdelta = mapa(sb, rank ^ 1) - sb;
  const int cid = blockIdx.x >> 1;
  const bool spare = cid < 2;
  const int pairi = cid - 2, batch = pairi >> 5, pp = pairi & 31;
  if (sb & 1023) TRAP(sb, 12345);
  if (tid == 0) {
    for (int i = 0; i < (int)NS; i++) { mbar_init(cx.full(i, 0), 1); mbar_init(cx.full(i, 1), 1); mbar_init(cx.empty(i), 8); }
    mbar_init(cx.afull(0), 1); mbar_init(cx.afull(1), 1);
    mbar_init(cx.afree(0), spare ? 4 : 8); mbar_init(cx.afree(1), 4);
    mbar_init(cx.gbar(), 16); mbar_init(cx.dbar(), 8);
    asm volatile("fence.mbarrier_init.release.cluster;" ::: "memory");
  }
  __syncthreads();
  cluster_arrive();

  if (warp >= 8) {
    reg_dealloc<24>();
    cluster_wait();
    const uint32_t ro = rank * 16384;
    if (warp == 8 && lane == 0) {
      if (spare) {
        if (mode != 2) {
          uint32_t n = 0;
#pragma unroll 1
          for (int j = 0; j < 8; j++)
#pragma unroll 1
            for (int i = 0; i < 16; i++, n++) {
              int w = i >> 3, kb = i & 7;
              uint32_t s = cx.acquire(n, w) + ro;
              if (j < 2) tma3d_mc(s, &maps.k, 256 * w + 128 * rank, kb, cx.full(n, w));
              else if (j == 2 || j == 4) tma3d_mc(s, &maps.ao, 64 * kb, 4 * w + 2 * rank, cx.full(n, w));
              else tma3d_mc(s, &maps.mg, (j >= 6 ? 512 : 0) + 64 * kb, 4 * w + 2 * rank, cx.full(n, w));
            }
        }
      } else if (mode != 1) {
        const uint32_t ep1 = ld_acquire(&g_flags[F_DONE * 32]) / NCTA + 1;
        uint32_t n = 0;
#pragma unroll 1
        for (; n < 32; n++) {
          uint32_t w = (n >> 3) & 1, s = cx.acquire(n, w) + ro;
          tma3d_mc(s, &maps.up, 64 * (n & 7), (n < 16 ? 8 : 0) + 4 * w + 2 * rank, cx.full(n, w));
        }
#pragma unroll 1
        for (; n < 48; n++) {
          int w = (n >> 3) & 1, kb = n & 7;
          wait_flag(F_WQK + 2 * kb + w, ep1 * 4);
          uint32_t s = cx.acquire(n, w) + ro;
          bulk_g2s_mc(s, g_wqk + kb * TILE + w * SLOT + ro, 16384, cx.full(n, w));
        }
        wait_flag(F_XA + batch, ep1 * 512);
        const uint8_t* kv = g_xa + (size_t)batch * NTILE * TILE + ro;
#pragma unroll 1
        for (; n < N_FIN0; n++) {
          uint32_t i = n - N_ATT0, t = i >> 1, h = (t ^ i) & 1;
          uint32_t s = cx.acquire(n, t & 1) + ro;
          bulk_g2s_mc(s, kv + (size_t)t * TILE + h * SLOT, 16384, cx.full(n, t & 1));
        }
        wait_flag(F_WF, ep1 * 128);
#pragma unroll 1
        for (; n < N_FIN0 + 32; n++) {
          uint32_t i = (n - N_FIN0) >> 1, w = (n - N_FIN0) & 1;
          uint32_t kb = i < 8 ? i : 8 + ((i + 4 * w) & 7);
          uint32_t s = cx.acquire(n, w) + ro;
          bulk_g2s_mc(s, g_wf + kb * TILE + w * SLOT + ro, 16384, cx.full(n, w));
        }
      }
    } else if (warp == 9 && lane == 0) {
      if (spare) {
        if (mode != 2) {
          const int s = 2 * cid + rank;
#pragma unroll 1
          for (int r = 0; r < 6; r++) {
            const CUtensorMap* m = r < 2 ? &maps.q : (r < 4 ? &maps.v : &maps.dn);
            int row = 64 * (s + 4 * (r & 1));
#pragma unroll 1
            for (int h = 0; h < 2; h++) {
              if (r > 0) mbar_wait(cx.afree(h), (r - 1) & 1);
              mbar_expect_tx(cx.afull(h), SLOT);
              tma3d(sb + OFF_Q + h * SLOT, m, row, 4 * h, cx.afull(h));
              tma3d(sb + OFF_Q + h * SLOT + 16384, m, row, 4 * h + 2, cx.afull(h));
            }
          }
        }
      } else if (mode != 1) {
        const uint8_t* uc = g_uc + (size_t)(2 * pairi + rank) * TILE;
        mbar_wait(cx.afree(0), 0);
        fence_async_all();
        mbar_expect_tx(cx.afull(0), 7 * CH);
        bulk_g2s(sb + OFF_Q, uc, 7 * CH, cx.afull(0));
        mbar_wait(cx.afree(1), 0);
        mbar_expect_tx(cx.afull(1), CH);
        bulk_g2s(sb + OFF_P, uc + 7 * CH, CH, cx.afull(1));
      }
    } else if (warp == 10 && lane == 0) {
      mbar_wait(cx.dbar(), 0);
    }
    __syncwarp();
    cluster_arrive();
    cluster_wait();
  } else {
    MARK(mode * 1000 + 500);
    reg_alloc<240>();
    MARK(mode * 1000 + 501);
    const int w = warp >> 2, wq = warp & 3, q = lane >> 2, c = lane & 3;
    cx.fb = cx.full(0, w); cx.ph = 0;
    const int rlo = 16 * wq + q;
    const int mrow = 16 * wq + (lane & 15);
    const uint32_t moff = mrow * 128, mx = mrow & 7, mu = lane >> 4;
    float acc[128];

    if (spare) {
      cluster_wait();
      if (mode != 2) {
        const int s = 2 * cid + rank;
        int ar = 0;
#pragma unroll 1
        for (int j = 0; j < 8; j++) {
          MARK(mode * 1000 + j * 10);
          const bool tmaA = (j != 3 && j != 5), t1 = (j == 2 || j == 4), nextTma = (j != 2 && j != 4 && j != 7);
          auto pre = [&](int kb) {
            if (tmaA && (kb & 3) == 0) mbar_wait(cx.afull(kb >> 2), ar & 1);
            if (!tmaA && kb == (w ? 0 : 4)) bar_sync(w ? 5 : 6);
          };
          auto post = [&](int kb) {
            if (w == 1 && (kb & 3) == 3) {
              if (nextTma) { if (lane == 0) mbar_arrive(cx.afree(kb >> 2)); }
              else if (t1 && kb == 3) bar_arrive(4);
            }
          };
          if (j < 2) gemm8<0>(cx, acc, 16 * j + 8 * w, 1, pre, post);
          else gemm8<1>(cx, acc, 16 * j + 8 * w, 1, pre, post);
          MARK(mode * 1000 + j * 10 + 1);
          if (tmaA) ar++;
          if (t1) {
            if (w == 0) bar_sync(4);
#pragma unroll
            for (int ks = 0; ks < 16; ks++)
              stsm4(sb + OFF_Q + (4 * w + (ks >> 2)) * CH + moff + (((2 * (ks & 3) + mu) ^ mx) << 4),
                    pack2(acc[8 * ks], acc[8 * ks + 1]), pack2(acc[8 * ks + 2], acc[8 * ks + 3]),
                    pack2(acc[8 * ks + 4], acc[8 * ks + 5]), pack2(acc[8 * ks + 6], acc[8 * ks + 7]));
            fence_async_smem();
            bar_arrive(w ? 6 : 5);
          } else {
            const int blk = s + 4 * (j < 2 ? j : (j < 6 ? (j >> 2) : (j & 1)));
            uint8_t* dst = j < 2 ? g_wqk + blk * TILE : g_wf + (j < 6 ? 8 + blk : blk) * TILE;
            const float sc = j < 2 ? 0.04419417382415922f * 1.4426950408889634f : 1.f;
            const int r0 = j >= 6 ? sigma(rlo) : rlo, r1 = j >= 6 ? sigma(rlo + 8) : rlo + 8;
#pragma unroll
            for (int i = 0; i < 8; i++) {
              uint8_t* d = dst + (4 * w + (i >> 1)) * CH;
              const int u = 4 * (i & 1) + c;
              *(uint4*)(d + r0 * 128 + ((u ^ (r0 & 7)) << 4)) =
                  make_uint4(pack2(acc[16 * i] * sc, acc[16 * i + 1] * sc), pack2(acc[16 * i + 4] * sc, acc[16 * i + 5] * sc),
                             pack2(acc[16 * i + 8] * sc, acc[16 * i + 9] * sc), pack2(acc[16 * i + 12] * sc, acc[16 * i + 13] * sc));
              *(uint4*)(d + r1 * 128 + ((u ^ (r1 & 7)) << 4)) =
                  make_uint4(pack2(acc[16 * i + 2] * sc, acc[16 * i + 3] * sc), pack2(acc[16 * i + 6] * sc, acc[16 * i + 7] * sc),
                             pack2(acc[16 * i + 10] * sc, acc[16 * i + 11] * sc), pack2(acc[16 * i + 14] * sc, acc[16 * i + 15] * sc));
            }
            signal_flag(j < 2 ? F_WQK + 2 * blk + w : F_WF);
          }
        }
      }
    } else {
      const int row0 = 125 * pp - 1 + 64 * (int)rank;
      const __nv_bfloat16* xb = x + (size_t)batch * TT * DD;
      {
        uint4 v[8][2];
#pragma unroll
        for (int i = 0; i < 8; i++) {
          int tr = row0 + 8 * warp + i;
          bool ok = tr >= 0 && tr < TT;
          const uint4* p = (const uint4*)(xb + (size_t)(ok ? tr : 0) * DD);
          v[i][0] = ok ? __ldg(p + lane) : make_uint4(0, 0, 0, 0);
          v[i][1] = ok ? __ldg(p + 32 + lane) : make_uint4(0, 0, 0, 0);
        }
        float mean[8], rs[8];
#pragma unroll
        for (int i = 0; i < 8; i++) {
          const uint32_t* u = (const uint32_t*)&v[i][0];
          float s = 0.f;
#pragma unroll
          for (int k = 0; k < 8; k++) s += blo(u[k]) + bhi(u[k]);
          mean[i] = s;
        }
#pragma unroll
        for (int o = 16; o; o >>= 1)
#pragma unroll
          for (int i = 0; i < 8; i++) mean[i] += __shfl_xor_sync(~0u, mean[i], o);
#pragma unroll
        for (int i = 0; i < 8; i++) {
          const uint32_t* u = (const uint32_t*)&v[i][0];
          mean[i] *= (1.f / DD);
          float s = 0.f;
#pragma unroll
          for (int k = 0; k < 8; k++) { float a = blo(u[k]) - mean[i], b = bhi(u[k]) - mean[i]; s = fmaf(a, a, s); s = fmaf(b, b, s); }
          rs[i] = s;
        }
#pragma unroll
        for (int o = 16; o; o >>= 1)
#pragma unroll
          for (int i = 0; i < 8; i++) rs[i] += __shfl_xor_sync(~0u, rs[i], o);
#pragma unroll
        for (int i = 0; i < 8; i++) {
          uint32_t* u = (uint32_t*)&v[i][0];
          float r = rsqrtf(rs[i] * (1.f / DD) + 1e-5f), mr = -mean[i] * r;
#pragma unroll
          for (int k = 0; k < 8; k++) u[k] = pack2(fmaf(blo(u[k]), r, mr), fmaf(bhi(u[k]), r, mr));
          uint32_t a = sb + OFF_Q + (lane >> 3) * CH + (8 * warp + i) * 128 + (((lane & 7) ^ i) << 4);
          sts128(a, u[0], u[1], u[2], u[3]);
          sts128(a + 4 * CH, u[4], u[5], u[6], u[7]);
        }
        fence_async_smem();
        if (mode != 2) {
          uint8_t* xg = g_xa + (size_t)batch * NTILE * TILE + (lane >> 3) * CH;
#pragma unroll
          for (int i = 0; i < 8; i++) {
            int L = 64 * (int)rank + 8 * warp + i, tr = row0 + 8 * warp + i;
            if (L >= 1 && L <= 125) {
              uint8_t* d = xg + (size_t)(tr >> 6) * TILE + (tr & 63) * 128 + (((lane & 7) ^ (tr & 7)) << 4);
              *(uint4*)d = v[i][0];
              *(uint4*)(d + 4 * CH) = v[i][1];
            }
          }
          if (pp == 31 && rank == 1) {
#pragma unroll
            for (int i = 0; i < 4; i++) {
              uint8_t* d = xg + (size_t)(NTILE - 1) * TILE + (32 + 4 * warp + i) * 128 + ((lane & 7) << 4);
              *(uint4*)d = make_uint4(0, 0, 0, 0);
              *(uint4*)(d + 4 * CH) = make_uint4(0, 0, 0, 0);
            }
          }
        }
      }
      cluster_wait();
      if (mode == 1) {
        signal_flag(F_XA + batch);
      } else {
        MARK(510);
        bar_sync(3);
        MARK(511);
        auto nop = [](int) {};
        uint32_t gp[64];
        gemm8<1>(cx, acc, 8 * w, 1, nop, nop);
        MARK(512);
        uint4* halo = g_halo + (size_t)((pairi * 2 + w) * 8) * 64;
        const int gw = 4 * (int)rank + wq;
        const uint32_t st = sb + OFF_EX;
        {
          float s1a = 0.f, s2a = 0.f, s1b = 0.f, s2b = 0.f;
#pragma unroll
          for (int j = 0; j < 32; j++) {
            float a0 = gelu(acc[4 * j]), a1 = gelu(acc[4 * j + 1]), b0 = gelu(acc[4 * j + 2]), b1 = gelu(acc[4 * j + 3]);
            s1a += a0 + a1; s2a = fmaf(a0, a0, s2a); s2a = fmaf(a1, a1, s2a);
            s1b += b0 + b1; s2b = fmaf(b0, b0, s2b); s2b = fmaf(b1, b1, s2b);
            gp[2 * j] = pack2(a0, a1); gp[2 * j + 1] = pack2(b0, b1);
          }
#pragma unroll
          for (int o = 1; o < 4; o <<= 1) {
            s1a += __shfl_xor_sync(~0u, s1a, o); s2a += __shfl_xor_sync(~0u, s2a, o);
            s1b += __shfl_xor_sync(~0u, s1b, o); s2b += __shfl_xor_sync(~0u, s2b, o);
          }
          if (c == 0) {
            uint32_t a = st + (w * 66 + 1 + rlo) * 8;
            asm volatile("st.shared.v2.f32 [%0], {%1, %2};" :: "r"(a), "f"(s1a), "f"(s2a) : "memory");
            asm volatile("st.shared.v2.f32 [%0], {%1, %2};" :: "r"(a + 64), "f"(s1b), "f"(s2b) : "memory");
            if (rank == 0 && rlo == 55) asm volatile("st.shared::cluster.v2.f32 [%0], {%1, %2};" :: "r"(st + w * 66 * 8 + cx.pdelta), "f"(s1b), "f"(s2b) : "memory");
            if (rank == 1 && rlo == 0) asm volatile("st.shared::cluster.v2.f32 [%0], {%1, %2};" :: "r"(st + (w * 66 + 65) * 8 + cx.pdelta), "f"(s1a), "f"(s2a) : "memory");
          }
          if (q == 0 || q == 7) {
            const int o = q ? 1 : 0;
#pragma unroll
            for (int i = 0; i < 8; i++)
              halo[(gw * 2 + o) * 32 + i * 4 + c] = q ? make_uint4(gp[8 * i + 1], gp[8 * i + 3], gp[8 * i + 5], gp[8 * i + 7])
                                                      : make_uint4(gp[8 * i], gp[8 * i + 2], gp[8 * i + 4], gp[8 * i + 6]);
          }
          if (mode == 0) signal_flag(F_XA + batch); else { __threadfence(); __syncwarp(); }
          if (lane == 0) { mbar_arrive_cluster_rel(mapa(cx.gbar(), 0)); mbar_arrive_cluster_rel(mapa(cx.gbar(), 1)); }
        }
        MARK(513);
        gemm8<1>(cx, acc, 16 + 8 * w, 1, nop, nop);
        MARK(514);
        {
          mbar_wait_cl(cx.gbar(), 0);
          float ra, ma, rb, mb, rh, mh;
          auto stat = [&](int idx, float& r, float& m) {
            float a0, a1, b0, b1;
            asm volatile("ld.shared.v2.f32 {%0, %1}, [%2];" : "=f"(a0), "=f"(a1) : "r"(st + idx * 8) : "memory");
            asm volatile("ld.shared.v2.f32 {%0, %1}, [%2];" : "=f"(b0), "=f"(b1) : "r"(st + (66 + idx) * 8) : "memory");
            float mu_ = (a0 + b0) * (1.f / DD);
            float var = fmaxf(fmaf(-mu_, mu_, (a1 + b1) * (1.f / DD)), 0.f);
            r = rsqrtf(var + 1e-5f); m = -mu_ * r;
          };
          stat(1 + rlo, ra, ma); stat(9 + rlo, rb, mb);
          const bool hv = (q == 0 && gw > 0) || (q == 7 && gw < 7);
          stat(q == 0 ? 16 * wq : 16 * wq + 17, rh, mh);
          if (!hv) { rh = 0.f; mh = 0.f; }
          const uint4* hp = halo + (q == 0 ? ((gw - 1) * 2 + 1) * 32 : (gw + 1) * 2 * 32) + c;
          const uint32_t* dwp = (const uint32_t*)dw + 128 * w + c;
          uint8_t* ucp = g_uc + (size_t)(2 * pairi + rank) * TILE + 4 * w * CH + rlo * 128;
          const int up = (lane + 28) & 31, dn = (lane + 4) & 31;
#pragma unroll
          for (int i = 0; i < 8; i++) {
            uint4 hr = make_uint4(0, 0, 0, 0);
            if (hv) hr = __ldcg(hp + i * 4);
            uint32_t hh[4] = {hr.x, hr.y, hr.z, hr.w}, oa[4], ob[4];
#pragma unroll
            for (int jj = 0; jj < 4; jj++) {
              const int j = 4 * i + jj;
              uint32_t d0 = __ldg(dwp + 4 * j), d1 = __ldg(dwp + 256 + 4 * j), d2 = __ldg(dwp + 512 + 4 * j);
              uint32_t lo = pack2(fmaf(blo(gp[2 * j]), ra, ma), fmaf(bhi(gp[2 * j]), ra, ma));
              uint32_t hi = pack2(fmaf(blo(gp[2 * j + 1]), rb, mb), fmaf(bhi(gp[2 * j + 1]), rb, mb));
              uint32_t hn = pack2(fmaf(blo(hh[jj]), rh, mh), fmaf(bhi(hh[jj]), rh, mh));
              uint32_t A = __shfl_sync(~0u, lo, up), B = __shfl_sync(~0u, hi, up);
              uint32_t C = __shfl_sync(~0u, lo, dn), E = __shfl_sync(~0u, hi, dn);
              uint32_t pl = q > 0 ? A : hn, ph = q > 0 ? B : A, nl = q < 7 ? C : E, nh = q < 7 ? E : hn;
              uint32_t ca = hfma2(nl, d2, hfma2(lo, d1, hmul2(pl, d0)));
              uint32_t cb = hfma2(nh, d2, hfma2(hi, d1, hmul2(ph, d0)));
              oa[jj] = hmul2(pack2(gelu(acc[4 * j]), gelu(acc[4 * j + 1])), ca);
              ob[jj] = hmul2(pack2(gelu(acc[4 * j + 2]), gelu(acc[4 * j + 3])), cb);
            }
            uint8_t* d = ucp + (i >> 1) * CH + (((4 * (i & 1) + c) ^ q) << 4);
            *(uint4*)d = make_uint4(oa[0], oa[1], oa[2], oa[3]);
            *(uint4*)(d + 1024) = make_uint4(ob[0], ob[1], ob[2], ob[3]);
          }
          fence_async_all();
        }
        MARK(515);
        gemm8<1>(cx, acc, 32 + 8 * w, 1, nop, [&](int kb) { if (w == 1 && kb == 3) bar_arrive(4); });
        MARK(516);
        if (w == 0) bar_sync(4);
#pragma unroll
        for (int i = 0; i < 8; i++) {
          uint32_t a = sb + OFF_Q + (4 * w + (i >> 1)) * CH + rlo * 128 + (((4 * (i & 1) + c) ^ q) << 4);
          sts128(a, pack2(acc[16 * i], acc[16 * i + 1]), pack2(acc[16 * i + 4], acc[16 * i + 5]),
                 pack2(acc[16 * i + 8], acc[16 * i + 9]), pack2(acc[16 * i + 12], acc[16 * i + 13]));
          sts128(a + 1024, pack2(acc[16 * i + 2], acc[16 * i + 3]), pack2(acc[16 * i + 6], acc[16 * i + 7]),
                 pack2(acc[16 * i + 10], acc[16 * i + 11]), pack2(acc[16 * i + 14], acc[16 * i + 15]));
        }
        fence_async_smem();
        uint32_t qf[16];
        if (w == 1) {
          __syncwarp();
#pragma unroll
          for (int ks = 0; ks < 4; ks++) ldsm4(sb + OFF_P + moff + (((2 * ks + mu) ^ mx) << 4), qf[4 * ks], qf[4 * ks + 1], qf[4 * ks + 2], qf[4 * ks + 3]);
        }
        bar_arrive(w ? 6 : 5);

#pragma unroll
        for (int i = 0; i < 128; i++) acc[i] = 0.f;
        float m0 = -INFINITY, m1 = -INFINITY, l0 = 0.f, l1 = 0.f;
        const uint32_t exa = sb + OFF_EX + (tid & 127) * 16;
        const uint64_t dq_own = desc_k(sb + OFF_Q + 4 * w * CH), dq_oth = desc_k(sb + OFF_Q + 3 * (1 - w) * CH), dp = desc_k(sb + OFF_P);
        float S[32];
        fence_regs(acc);
        auto recv = [&]() {
          bar_sync(2 - w);
          float a, b;
          asm volatile("ld.shared.v4.f32 {%0, %1, %2, %3}, [%4];" : "=f"(a), "=f"(b), "=f"(l0), "=f"(l1) : "r"(exa) : "memory");
          if (__any_sync(~0u, a != m0 || b != m1)) {
            float f0 = ex2(m0 - a), f1 = ex2(m1 - b);
#pragma unroll
            for (int j = 0; j < 32; j++) { acc[4 * j] *= f0; acc[4 * j + 1] *= f0; acc[4 * j + 2] *= f1; acc[4 * j + 3] *= f1; }
          }
          m0 = a; m1 = b;
        };
#pragma unroll 1
        for (int t = w; t < NTILE; t += 2) {
          const uint32_t n = N_ATT0 + 2 * t;
          MARK(600 + t);
          cx.wait_full(n);
          const uint64_t dko = desc_k(cx.slot(n)), dkx = desc_k(cx.slot(n + 1));
          wg_fence();
#pragma unroll
          for (int k = 0; k < 12; k++) wgmma_ss_n64_tb0(S, dq_own + (k >> 2) * 512 + (k & 3) * 2, dko + (k >> 2) * 512 + (k & 3) * 2, k != 0);
          wg_commit();
          wg_wait<1>();
          fence_regs(acc);
          if (t >= 2) cx.release(n - 4);
          else {
            bar_sync(w ? 5 : 6);
            if (w == 0) {
#pragma unroll
              for (int ks = 0; ks < 4; ks++) ldsm4(sb + OFF_P + moff + (((2 * ks + mu) ^ mx) << 4), qf[4 * ks], qf[4 * ks + 1], qf[4 * ks + 2], qf[4 * ks + 3]);
            }
          }
          cx.wait_full(n + 1);
          {
            const uint64_t dr = (w ? dko : dkx) + 1536, d0 = w ? dkx : dko + 1536, d1 = w ? dkx : dkx - 512;
            wg_fence();
#pragma unroll
            for (int k = 0; k < 4; k++) wgmma_rs_n64_tb0(S, qf[4 * k], qf[4 * k + 1], qf[4 * k + 2], qf[4 * k + 3], dr + k * 2, 1);
#pragma unroll
            for (int k = 0; k < 4; k++) wgmma_ss_n64_tb0(S, dq_oth + k * 2, d0 + k * 2, 1);
#pragma unroll
            for (int k = 4; k < 16; k++) wgmma_ss_n64_tb0(S, dq_oth + (k >> 2) * 512 + (k & 3) * 2, d1 + (k >> 2) * 512 + (k & 3) * 2, 1);
            wg_commit();
          }
          if (t > 0) {
            recv();
            const uint64_t db = desc_mn(cx.slot(n - 1));
            wg_fence();
#pragma unroll
            for (int k = 0; k < 4; k++) wgmma_ss_n256_tb1(acc, dp + k * 2, db + k * 128, 1);
            wg_commit();
            wg_wait<1>();
          } else {
            wg_wait<0>();
          }
          fence_regs(S);
          if (t >= NTILE - 2 && lane == 0) mbar_arrive(cx.afree(0));
          if (t == NTILE - 1) {
#pragma unroll
            for (int i = 16; i < 32; i++) S[i] = -INFINITY;
          }
          float x0 = fmaxf(S[0], S[1]), x1 = fmaxf(S[2], S[3]);
#pragma unroll
          for (int j = 1; j < 8; j++) { x0 = fmaxf(x0, fmaxf(S[4 * j], S[4 * j + 1])); x1 = fmaxf(x1, fmaxf(S[4 * j + 2], S[4 * j + 3])); }
          x0 = fmaxf(x0, __shfl_xor_sync(~0u, x0, 1)); x1 = fmaxf(x1, __shfl_xor_sync(~0u, x1, 1));
          x0 = fmaxf(x0, __shfl_xor_sync(~0u, x0, 2)); x1 = fmaxf(x1, __shfl_xor_sync(~0u, x1, 2));
          x0 = fmaxf(x0, m0); x1 = fmaxf(x1, m1);
          const bool chg = __any_sync(~0u, x0 != m0 || x1 != m1);
          const float f0 = ex2(m0 - x0), f1 = ex2(m1 - x1);
          m0 = x0; m1 = x1;
          uint32_t P[16];
          float s0 = 0.f, s1 = 0.f;
#pragma unroll
          for (int j = 0; j < 8; j++) {
            float a0 = ex2(S[4 * j] - x0), a1 = ex2(S[4 * j + 1] - x0), b0 = ex2(S[4 * j + 2] - x1), b1 = ex2(S[4 * j + 3] - x1);
            s0 += a0 + a1; s1 += b0 + b1;
            P[2 * j] = pack2(a0, a1); P[2 * j + 1] = pack2(b0, b1);
          }
          l0 = fmaf(l0, f0, s0); l1 = fmaf(l1, f1, s1);
          wg_wait<0>();
          fence_regs(acc);
          if (t > 0) cx.release(n - 1);
#pragma unroll
          for (int ks = 0; ks < 4; ks++) stsm4(sb + OFF_P + moff + (((2 * ks + mu) ^ mx) << 4), P[4 * ks], P[4 * ks + 1], P[4 * ks + 2], P[4 * ks + 3]);
          asm volatile("st.shared.v4.f32 [%0], {%1, %2, %3, %4};" :: "r"(exa), "f"(m0), "f"(m1), "f"(l0), "f"(l1) : "memory");
          fence_async_smem();
          bar_arrive(1 + w);
          if (chg) {
#pragma unroll
            for (int j = 0; j < 32; j++) { acc[4 * j] *= f0; acc[4 * j + 1] *= f0; acc[4 * j + 2] *= f1; acc[4 * j + 3] *= f1; }
          }
          {
            const uint64_t db = desc_mn(cx.slot(n));
            wg_fence();
#pragma unroll
            for (int k = 0; k < 4; k++) wgmma_rs_n256_tb1(acc, P[4 * k], P[4 * k + 1], P[4 * k + 2], P[4 * k + 3], db + k * 128, 1);
            wg_commit();
          }
        }
        wg_wait<0>();
        fence_regs(acc);
        cx.release(N_ATT0 + 2 * (NTILE - 1 - w));
        if (w == 1) {
          recv();
          const uint32_t n = N_ATT0 + 2 * (NTILE - 1) + 1;
          const uint64_t db = desc_mn(cx.slot(n));
          wg_fence();
#pragma unroll
          for (int k = 0; k < 4; k++) wgmma_ss_n256_tb1(acc, dp + k * 2, db + k * 128, 1);
          wg_commit();
          wg_wait<0>();
          fence_regs(acc);
          cx.release(n);
          if (lane == 0) mbar_arrive(cx.afree(1));
        }
        l0 += __shfl_xor_sync(~0u, l0, 1); l1 += __shfl_xor_sync(~0u, l1, 1);
        l0 += __shfl_xor_sync(~0u, l0, 2); l1 += __shfl_xor_sync(~0u, l1, 2);
        {
          const float i0 = 1.f / l0, i1 = 1.f / l1;
#pragma unroll
          for (int j = 0; j < 32; j++) { gp[2 * j] = pack2(acc[4 * j] * i0, acc[4 * j + 1] * i0); gp[2 * j + 1] = pack2(acc[4 * j + 2] * i1, acc[4 * j + 3] * i1); }
        }
        const uint32_t nf = N_FIN0 + w;
#pragma unroll 1
        for (int kb = 0; kb < 8; kb++) {
          const uint32_t n = nf + 2 * kb;
          if (kb == 0) mbar_wait(cx.afull(0), 0);
          if (kb == 7) mbar_wait(cx.afull(1), 0);
          cx.wait_full(n);
          const uint64_t da = desc_k(sb + OFF_Q + kb * CH), db = desc_mn(cx.slot(n));
          wg_fence();
#pragma unroll
          for (int k = 0; k < 4; k++) wgmma_ss_n256_tb1(acc, da + k * 2, db + k * 128, (kb | k) != 0);
          wg_commit();
          if (kb > 0) { wg_wait<1>(); cx.release(n - 2); }
        }
#pragma unroll
        for (int kb = 0; kb < 4; kb++) {
          const uint32_t n = nf + 16 + 2 * kb;
          cx.wait_full(n);
          const uint64_t db = desc_mn(cx.slot(n));
          wg_fence();
#pragma unroll
          for (int k = 0; k < 4; k++) wgmma_rs_n256_tb1(acc, gp[16 * kb + 4 * k], gp[16 * kb + 4 * k + 1], gp[16 * kb + 4 * k + 2], gp[16 * kb + 4 * k + 3], db + k * 128, 1);
          wg_commit();
          wg_wait<1>();
          cx.release(n - 2);
          if (kb == 0) bar_arrive(7 + w);
          if (kb == 1) {
            bar_sync(8 - w);
#pragma unroll
            for (int ks = 0; ks < 16; ks++)
              stsm4(sb + OFF_Q + (4 * w + (ks >> 2)) * CH + moff + (((2 * (ks & 3) + mu) ^ mx) << 4), gp[4 * ks], gp[4 * ks + 1], gp[4 * ks + 2], gp[4 * ks + 3]);
            fence_async_smem();
            bar_arrive(9 + w);
          }
        }
        bar_sync(10 - w);
        const int La = 64 * (int)rank + rlo, Lb = La + 8;
        const bool va = La >= 1 && La <= 125, vb = Lb <= 125;
        const size_t goff = ((size_t)batch * TT + row0 + rlo) * DD + 256 * w + 8 * c;
        uint4 xa[8], xc[8];
#pragma unroll
        for (int kb = 0; kb < 4; kb++) {
          const uint32_t n = nf + 24 + 2 * kb;
          cx.wait_full(n);
          const uint64_t da = desc_k(sb + OFF_Q + (4 * (1 - w) + kb) * CH), db = desc_mn(cx.slot(n));
          wg_fence();
#pragma unroll
          for (int k = 0; k < 4; k++) wgmma_ss_n256_tb1(acc, da + k * 2, db + k * 128, 1);
          wg_commit();
          wg_wait<1>();
          cx.release(n - 2);
          if (kb == 0) {
            fence_regs(gp);
#pragma unroll
            for (int i = 0; i < 8; i++) {
              xa[i] = va ? __ldg((const uint4*)(x + goff + 32 * i)) : make_uint4(0, 0, 0, 0);
              xc[i] = vb ? __ldg((const uint4*)(x + goff + 8 * DD + 32 * i)) : make_uint4(0, 0, 0, 0);
            }
          }
        }
        wg_wait<0>();
        fence_regs(acc);
#pragma unroll
        for (int i = 0; i < 8; i++) {
          const uint32_t* a = (const uint32_t*)&xa[i];
          const uint32_t* b = (const uint32_t*)&xc[i];
          uint4 oa, ob;
          oa.x = pack2(acc[16 * i] + blo(a[0]), acc[16 * i + 1] + bhi(a[0])); oa.y = pack2(acc[16 * i + 4] + blo(a[1]), acc[16 * i + 5] + bhi(a[1]));
          oa.z = pack2(acc[16 * i + 8] + blo(a[2]), acc[16 * i + 9] + bhi(a[2])); oa.w = pack2(acc[16 * i + 12] + blo(a[3]), acc[16 * i + 13] + bhi(a[3]));
          ob.x = pack2(acc[16 * i + 2] + blo(b[0]), acc[16 * i + 3] + bhi(b[0])); ob.y = pack2(acc[16 * i + 6] + blo(b[1]), acc[16 * i + 7] + bhi(b[1]));
          ob.z = pack2(acc[16 * i + 10] + blo(b[2]), acc[16 * i + 11] + bhi(b[2])); ob.w = pack2(acc[16 * i + 14] + blo(b[3]), acc[16 * i + 15] + bhi(b[3]));
          if (va) *(uint4*)(out + goff + 32 * i) = oa;
          if (vb) *(uint4*)(out + goff + 8 * DD + 32 * i) = ob;
        }
      }
    }
    MARK(mode * 1000 + 999);
    if (lane == 0) mbar_arrive(cx.dbar());
    if (tid == 0 && mode != 1) atomicAdd(&g_flags[F_DONE * 32], 1u);
    __syncwarp();
    cluster_arrive();
    cluster_wait();
  }
}

typedef CUresult (*EncodeFn)(CUtensorMap*, CUtensorMapDataType, cuuint32_t, void*, const cuuint64_t*, const cuuint64_t*, const cuuint32_t*,
                             const cuuint32_t*, CUtensorMapInterleave, CUtensorMapSwizzle, CUtensorMapL2promotion, CUtensorMapFloatOOBfill);

static void make_map(EncodeFn fn, CUtensorMap* m, void* p, int rows, int cols, int box_rows, int box_blks) {
  cuuint64_t dims[3] = {64, (cuuint64_t)rows, (cuuint64_t)(cols / 64)};
  cuuint64_t strides[2] = {(cuuint64_t)cols * 2, 128};
  cuuint32_t box[3] = {64, (cuuint32_t)box_rows, (cuuint32_t)box_blks};
  cuuint32_t es[3] = {1, 1, 1};
  fn(m, CU_TENSOR_MAP_DATA_TYPE_BFLOAT16, 3, p, dims, strides, box, es, CU_TENSOR_MAP_INTERLEAVE_NONE, CU_TENSOR_MAP_SWIZZLE_128B,
     CU_TENSOR_MAP_L2_PROMOTION_L2_256B, CU_TENSOR_MAP_FLOAT_OOB_FILL_NONE);
}

}

extern "C" void kernel_launch(void* const* d_in, const int* in_sizes, int n_in, void* d_out, int out_size) {
  using namespace bf;
  static EncodeFn fn = nullptr;
  static int fused = 0;
  if (!fn) {
    void* p = nullptr;
    cudaDriverEntryPointQueryResult qr;
    cudaGetDriverEntryPoint("cuTensorMapEncodeTiled", &p, cudaEnableDefault, &qr);
    fn = (EncodeFn)p;
    cudaFuncSetAttribute(bf_kernel, cudaFuncAttributeMaxDynamicSharedMemorySize, SMEM_BYTES);
    cudaLaunchConfig_t cfg = {};
    cfg.gridDim = dim3(NCTA); cfg.blockDim = dim3(384); cfg.dynamicSmemBytes = SMEM_BYTES;
    cudaLaunchAttribute at[1];
    at[0].id = cudaLaunchAttributeClusterDimension; at[0].val.clusterDim.x = 2; at[0].val.clusterDim.y = 1; at[0].val.clusterDim.z = 1;
    cfg.attrs = at; cfg.numAttrs = 1;
    int nc = 0;
    cudaOccupancyMaxActiveClusters(&nc, bf_kernel, &cfg);
    fused = nc >= NCTA / 2;
  }
  Maps maps;
  make_map(fn, &maps.q, d_in[1], 512, 512, 64, 2);
  make_map(fn, &maps.k, d_in[2], 512, 512, 128, 1);
  make_map(fn, &maps.v, d_in[3], 512, 512, 64, 2);
  make_map(fn, &maps.ao, d_in[4], 512, 512, 64, 2);
  make_map(fn, &maps.up, d_in[5], 512, 1024, 64, 2);
  make_map(fn, &maps.dn, d_in[7], 512, 512, 64, 2);
  make_map(fn, &maps.mg, d_in[8], 1024, 512, 64, 2);
  const __nv_bfloat16* x = (const __nv_bfloat16*)d_in[0];
  const __nv_bfloat16* dw = (const __nv_bfloat16*)d_in[6];
  __nv_bfloat16* out = (__nv_bfloat16*)d_out;
  if (fused) {
    bf_kernel<<<NCTA, 384, SMEM_BYTES>>>(maps, x, dw, out, 0);
  } else {
    bf_kernel<<<NCTA, 384, SMEM_BYTES>>>(maps, x, dw, out, 1);
    bf_kernel<<<NCTA, 384, SMEM_BYTES>>>(maps, x, dw, out, 2);
  }
}
```

```cpp
#include <cuda_runtime.h>
#include <cuda_bf16.h>
#include <cuda.h>
#include <stdint.h>

namespace bf {

constexpr int TT = 4000, DD = 512, NTILE = 63;
constexpr uint32_t CH = 8192, SLOT = 32768, NS = 5, TILE = 65536;
constexpr uint32_t OFF_Q = NS * SLOT;
constexpr uint32_t OFF_P = OFF_Q + 7 * CH;
constexpr uint32_t OFF_EX = OFF_Q + TILE;
constexpr uint32_t OFF_BAR = OFF_EX + 2048;
constexpr uint32_t SMEM_BYTES = OFF_BAR + 256;
constexpr int NCTA = 132;
#define PXS 4
#define MIDJ 4
#define QKA 3
#define CREG 232
#define PREG 40
#define XPACE 400
#define STG(p, v) __stcg(p, v)
#define RELALL 0
#define NOCONV 0
#define LAZY 8.f
constexpr uint32_t N_ATT0 = 48, N_FIN0 = 48 + 2 * NTILE;

struct Maps { CUtensorMap x, up, q, k, xs, xl, v, ao, dn, mg; };
struct Ptrs { const uint8_t *wq, *wk, *wv, *wao, *wup, *wdn, *wmg; };

__device__ __align__(1024) uint8_t g_xa[2 * (TT + 1) * DD * 2];
__device__ __align__(1024) uint8_t g_uc[256 * TILE];
__device__ __align__(1024) uint8_t g_wqk[8 * TILE];
__device__ __align__(1024) uint8_t g_wf[16 * TILE];
__device__ __align__(1024) float2 g_st[128 * 64 * 2];
__device__ uint32_t g_flags[8 * 32];
constexpr int F_WQK = 0, F_XA = 4, F_WF = 6, F_DONE = 7;

__device__ __forceinline__ uint32_t smem_u32(const void* p) { return (uint32_t)__cvta_generic_to_shared(p); }
__device__ __forceinline__ void mbar_init(uint32_t bar, uint32_t cnt) { asm volatile("mbarrier.init.shared::cta.b64 [%0], %1;" :: "r"(bar), "r"(cnt)); }
__device__ __forceinline__ void mbar_expect_tx(uint32_t bar, uint32_t bytes) { asm volatile("mbarrier.arrive.expect_tx.shared::cta.b64 _, [%0], %1;" :: "r"(bar), "r"(bytes) : "memory"); }
__device__ __forceinline__ void mbar_arrive(uint32_t bar) { asm volatile("mbarrier.arrive.shared::cta.b64 _, [%0];" :: "r"(bar) : "memory"); }
__device__ __forceinline__ void mbar_arrive_cluster(uint32_t a) { asm volatile("mbarrier.arrive.shared::cluster.b64 _, [%0];" :: "r"(a) : "memory"); }
__device__ __forceinline__ void mbar_arrive_cluster_rel(uint32_t a) { asm volatile("mbarrier.arrive.release.cluster.shared::cluster.b64 _, [%0];" :: "r"(a) : "memory"); }
__device__ __forceinline__ bool mbar_try_wait(uint32_t bar, uint32_t parity) {
  uint32_t ok;
  asm volatile("{\n.reg .pred p;\nmbarrier.try_wait.parity.shared::cta.b64 p, [%1], %2;\nselp.b32 %0, 1, 0, p;\n}\n" : "=r"(ok) : "r"(bar), "r"(parity) : "memory");
  return ok;
}
__device__ __forceinline__ bool mbar_try_wait_cl(uint32_t bar, uint32_t parity) {
  uint32_t ok;
  asm volatile("{\n.reg .pred p;\nmbarrier.try_wait.parity.acquire.cluster.shared::cta.b64 p, [%1], %2;\nselp.b32 %0, 1, 0, p;\n}\n" : "=r"(ok) : "r"(bar), "r"(parity) : "memory");
  return ok;
}
#define TRAP(a, b) __trap()
#define MARK(c)
#define STAMP(i)
#define PSTAMP(h, i)
#define GSTAMP(i)
#define FSTAMP(i)
__device__ __forceinline__ void mbar_wait(uint32_t bar, uint32_t parity) {
  asm volatile("{\n.reg .pred p;\n.reg .u32 c;\nmov.u32 c, 0;\nWL:\nmbarrier.try_wait.parity.shared::cta.b64 p, [%0], %1;\n@p bra WD;\n"
               "add.u32 c, c, 1;\nsetp.lt.u32 p, c, 0x400000;\n@p bra WL;\ntrap;\nWD:\n}\n" :: "r"(bar), "r"(parity) : "memory");
}
__device__ __forceinline__ void mbar_wait_cl(uint32_t bar, uint32_t parity) {
  asm volatile("{\n.reg .pred p;\n.reg .u32 c;\nmov.u32 c, 0;\nWL:\nmbarrier.try_wait.parity.acquire.cluster.shared::cta.b64 p, [%0], %1;\n@p bra WD;\n"
               "add.u32 c, c, 1;\nsetp.lt.u32 p, c, 0x400000;\n@p bra WL;\ntrap;\nWD:\n}\n" :: "r"(bar), "r"(parity) : "memory");
}
__device__ __forceinline__ uint32_t mapa(uint32_t addr, uint32_t rank) { uint32_t r; asm volatile("mapa.shared::cluster.u32 %0, %1, %2;" : "=r"(r) : "r"(addr), "r"(rank)); return r; }
__device__ __forceinline__ void bulk_g2s(uint32_t dst, const void* src, uint32_t bytes, uint32_t bar) {
  asm volatile("cp.async.bulk.shared::cluster.global.mbarrier::complete_tx::bytes [%0], [%1], %2, [%3];" :: "r"(dst), "l"(src), "r"(bytes), "r"(bar) : "memory");
}
__device__ __forceinline__ void bulk_g2s_mc(uint32_t dst, const void* src, uint32_t bytes, uint32_t bar) {
  asm volatile("cp.async.bulk.shared::cluster.global.mbarrier::complete_tx::bytes.multicast::cluster [%0], [%1], %2, [%3], %4;" :: "r"(dst), "l"(src), "r"(bytes), "r"(bar), "h"((uint16_t)3) : "memory");
}
__device__ __forceinline__ void tma3d(uint32_t dst, const CUtensorMap* m, int c1, int c2, uint32_t bar) {
  asm volatile("cp.async.bulk.tensor.3d.shared::cluster.global.mbarrier::complete_tx::bytes [%0], [%1, {%3, %4, %5}], [%2];"
               :: "r"(dst), "l"(m), "r"(bar), "r"(0), "r"(c1), "r"(c2) : "memory");
}
__device__ __forceinline__ void tma3d_mc(uint32_t dst, const CUtensorMap* m, int c1, int c2, uint32_t bar) {
  asm volatile("cp.async.bulk.tensor.3d.shared::cluster.global.mbarrier::complete_tx::bytes.multicast::cluster [%0], [%1, {%3, %4, %5}], [%2], %6;"
               :: "r"(dst), "l"(m), "r"(bar), "r"(0), "r"(c1), "r"(c2), "h"((uint16_t)3) : "memory");
}
__device__ __forceinline__ void tma4d(uint32_t dst, const CUtensorMap* m, int c1, int c2, int c3, uint32_t bar) {
  asm volatile("cp.async.bulk.tensor.4d.shared::cluster.global.mbarrier::complete_tx::bytes [%0], [%1, {%3, %4, %5, %6}], [%2];"
               :: "r"(dst), "l"(m), "r"(bar), "r"(0), "r"(c1), "r"(c2), "r"(c3) : "memory");
}
__device__ __forceinline__ void tma4d_mc(uint32_t dst, const CUtensorMap* m, int c1, int c2, int c3, uint32_t bar) {
  asm volatile("cp.async.bulk.tensor.4d.shared::cluster.global.mbarrier::complete_tx::bytes.multicast::cluster [%0], [%1, {%3, %4, %5, %6}], [%2], %7;"
               :: "r"(dst), "l"(m), "r"(bar), "r"(0), "r"(c1), "r"(c2), "r"(c3), "h"((uint16_t)3) : "memory");
}
__device__ __forceinline__ void tma4d_store(const CUtensorMap* m, uint32_t src, int c1, int c2, int c3) {
  asm volatile("cp.async.bulk.tensor.4d.global.shared::cta.bulk_group [%0, {%2, %3, %4, %5}], [%1];"
               :: "l"(m), "r"(src), "r"(0), "r"(c1), "r"(c2), "r"(c3) : "memory");
}
__device__ __forceinline__ void l2_prefetch(const void* p, uint32_t bytes) { asm volatile("cp.async.bulk.prefetch.L2.global [%0], %1;" :: "l"(p), "r"(bytes) : "memory"); }
__device__ __forceinline__ void map_prefetch(const CUtensorMap* m) { asm volatile("prefetch.tensormap [%0];" :: "l"(m) : "memory"); }
__device__ __forceinline__ bool elect_one() {
  uint32_t p;
  asm volatile("{\n.reg .pred P;\nelect.sync _|P, 0xffffffff;\nselp.b32 %0, 1, 0, P;\n}\n" : "=r"(p));
  return p;
}
__device__ __forceinline__ void wg_fence() { asm volatile("wgmma.fence.sync.aligned;" ::: "memory"); }
__device__ __forceinline__ void wg_commit() { asm volatile("wgmma.commit_group.sync.aligned;" ::: "memory"); }
template <int N> __device__ __forceinline__ void wg_wait() { asm volatile("wgmma.wait_group.sync.aligned %0;" :: "n"(N) : "memory"); }
__device__ __forceinline__ void cluster_arrive() { asm volatile("barrier.cluster.arrive.aligned;" ::: "memory"); }
__device__ __forceinline__ void cluster_wait() { asm volatile("barrier.cluster.wait.aligned;" ::: "memory"); }
__device__ __forceinline__ uint32_t cluster_rank() { uint32_t r; asm volatile("mov.u32 %0, %%cluster_ctarank;" : "=r"(r)); return r; }
__device__ __forceinline__ void bar_sync(int id) { asm volatile("bar.sync %0, 256;" :: "r"(id) : "memory"); }
__device__ __forceinline__ void bar_sync_n(int id, int n) { asm volatile("bar.sync %0, %1;" :: "r"(id), "r"(n) : "memory"); }
__device__ __forceinline__ void bar_arrive(int id) { asm volatile("bar.arrive %0, 256;" :: "r"(id) : "memory"); }
__device__ __forceinline__ void fence_async_smem() { asm volatile("fence.proxy.async.shared::cta;" ::: "memory"); }
__device__ __forceinline__ void fence_async_all() { asm volatile("fence.proxy.async;" ::: "memory"); }
__device__ __forceinline__ uint32_t desc_k(uint32_t addr) { return ((addr & 0x3FFFF) >> 4) | (1u << 16); }
__device__ __forceinline__ uint32_t desc_mn(uint32_t addr) { return ((addr & 0x3FFFF) >> 4) | ((CH >> 4) << 16); }
template <int R> __device__ __forceinline__ void reg_alloc() { asm volatile("setmaxnreg.inc.sync.aligned.u32 %0;" :: "n"(R)); }
template <int R> __device__ __forceinline__ void reg_dealloc() { asm volatile("setmaxnreg.dec.sync.aligned.u32 %0;" :: "n"(R)); }
template <int N> __device__ __forceinline__ void fence_regs(float (&r)[N]) {
#pragma unroll
  for (int i = 0; i < N; i++) asm volatile("" : "+f"(r[i]) :: "memory");
}
template <int N> __device__ __forceinline__ void fence_regs(uint32_t (&r)[N]) {
#pragma unroll
  for (int i = 0; i < N; i++) asm volatile("" : "+r"(r[i]) :: "memory");
}
template <int N> __device__ __forceinline__ void zero_regs(float (&r)[N]) {
#pragma unroll
  for (int i = 0; i < N; i++) r[i] = 0.f;
  fence_regs(r);
}
__device__ __forceinline__ uint32_t pack2(float lo, float hi) { uint32_t r; asm("cvt.rn.bf16x2.f32 %0, %1, %2;" : "=r"(r) : "f"(hi), "f"(lo)); return r; }
__device__ __forceinline__ float blo(uint32_t v) { return __uint_as_float(v << 16); }
__device__ __forceinline__ float bhi(uint32_t v) { return __uint_as_float(v & 0xFFFF0000u); }
__device__ __forceinline__ float ex2(float x) { float r; asm("ex2.approx.ftz.f32 %0, %1;" : "=f"(r) : "f"(x)); return r; }
__device__ __forceinline__ float gelu(float x) {
  float z = x * fmaf(x * x, 0.044715f * 0.7978845608028654f, 0.7978845608028654f), t;
  asm("tanh.approx.f32 %0, %1;" : "=f"(t) : "f"(z));
  float h = 0.5f * x;
  return fmaf(h, t, h);
}
__device__ __forceinline__ uint32_t hfma2(uint32_t a, uint32_t b, uint32_t c) { uint32_t r; asm("fma.rn.bf16x2 %0, %1, %2, %3;" : "=r"(r) : "r"(a), "r"(b), "r"(c)); return r; }
__device__ __forceinline__ uint32_t hmul2(uint32_t a, uint32_t b) { uint32_t r; asm("mul.rn.bf16x2 %0, %1, %2;" : "=r"(r) : "r"(a), "r"(b)); return r; }
__device__ __forceinline__ void stsm4(uint32_t addr, uint32_t a, uint32_t b, uint32_t c, uint32_t d) {
  asm volatile("stmatrix.sync.aligned.m8n8.x4.shared.b16 [%0], {%1, %2, %3, %4};" :: "r"(addr), "r"(a), "r"(b), "r"(c), "r"(d) : "memory");
}
__device__ __forceinline__ void ldsm4(uint32_t addr, uint32_t& a, uint32_t& b, uint32_t& c, uint32_t& d) {
  asm volatile("ldmatrix.sync.aligned.m8n8.x4.shared.b16 {%0, %1, %2, %3}, [%4];" : "=r"(a), "=r"(b), "=r"(c), "=r"(d) : "r"(addr) : "memory");
}
__device__ __forceinline__ void sts128(uint32_t addr, uint32_t a, uint32_t b, uint32_t c, uint32_t d) {
  asm volatile("st.shared.v4.b32 [%0], {%1, %2, %3, %4};" :: "r"(addr), "r"(a), "r"(b), "r"(c), "r"(d) : "memory");
}
__device__ __forceinline__ void lds128(uint32_t addr, uint32_t (&v)[4]) {
  asm volatile("ld.shared.v4.b32 {%0, %1, %2, %3}, [%4];" : "=r"(v[0]), "=r"(v[1]), "=r"(v[2]), "=r"(v[3]) : "r"(addr) : "memory");
}
__device__ __forceinline__ uint32_t ld_relaxed(const uint32_t* p) { uint32_t v; asm volatile("ld.relaxed.gpu.global.u32 %0, [%1];" : "=r"(v) : "l"(p) : "memory"); return v; }
__device__ __forceinline__ int fresh_tid() { int t; asm volatile("mov.u32 %0, %%tid.x;" : "=r"(t)); return t; }
__device__ __forceinline__ void fence_gpu() { asm volatile("fence.acq_rel.gpu;" ::: "memory"); }
__device__ __forceinline__ void wait_flag(int idx, uint32_t target) {
  uint32_t i = 0;
#pragma unroll 1
  while ((int)(ld_relaxed(&g_flags[idx * 32]) - target) < 0) { __nanosleep(idx == F_WF ? 1000 : 32); if (++i > (1u << 22)) TRAP(idx, target); }
  fence_async_all();
}
__device__ __forceinline__ void signal_flag(int idx) {
  fence_async_all();
  fence_gpu();
  asm volatile("red.relaxed.gpu.global.add.u32 [%0], 1;" :: "l"(&g_flags[idx * 32]) : "memory");
}

__device__ __forceinline__ void wgmma_ss_n256_tb1(float (&d)[128], uint32_t da, uint32_t db, int scale_d) {
  asm volatile("{\n.reg .pred p;\n.reg .b64 da, db;\nsetp.ne.b32 p, %130, 0;\nmov.b64 da, {%128, 0x40000040};\nmov.b64 db, {%129, 0x40000040};\n"
    "wgmma.mma_async.sync.aligned.m64n256k16.f32.bf16.bf16 {%0, %1, %2, %3, %4, %5, %6, %7, %8, %9, %10, %11, %12, %13, %14, %15, %16, %17, %18, %19, %20, %21, %22, %23, %24, %25, %26, %27, %28, %29, %30, %31, %32, %33, %34, %35, %36, %37, %38, %39, %40, %41, %42, %43, %44, %45, %46, %47, %48, %49, %50, %51, %52, %53, %54, %55, %56, %57, %58, %59, %60, %61, %62, %63, %64, %65, %66, %67, %68, %69, %70, %71, %72, %73, %74, %75, %76, %77, %78, %79, %80, %81, %82, %83, %84, %85, %86, %87, %88, %89, %90, %91, %92, %93, %94, %95, %96, %97, %98, %99, %100, %101, %102, %103, %104, %105, %106, %107, %108, %109, %110, %111, %112, %113, %114, %115, %116, %117, %118, %119, %120, %121, %122, %123, %124, %125, %126, %127}, da, db, p, 1, 1, 0, 1;\n}\n"
    : "+f"(d[0]), "+f"(d[1]), "+f"(d[2]), "+f"(d[3]), "+f"(d[4]), "+f"(d[5]), "+f"(d[6]), "+f"(d[7]), "+f"(d[8]), "+f"(d[9]), "+f"(d[10]), "+f"(d[11]), "+f"(d[12]), "+f"(d[13]), "+f"(d[14]), "+f"(d[15]), "+f"(d[16]), "+f"(d[17]), "+f"(d[18]), "+f"(d[19]), "+f"(d[20]), "+f"(d[21]), "+f"(d[22]), "+f"(d[23]), "+f"(d[24]), "+f"(d[25]), "+f"(d[26]), "+f"(d[27]), "+f"(d[28]), "+f"(d[29]), "+f"(d[30]), "+f"(d[31]), "+f"(d[32]), "+f"(d[33]), "+f"(d[34]), "+f"(d[35]), "+f"(d[36]), "+f"(d[37]), "+f"(d[38]), "+f"(d[39]), "+f"(d[40]), "+f"(d[41]), "+f"(d[42]), "+f"(d[43]), "+f"(d[44]), "+f"(d[45]), "+f"(d[46]), "+f"(d[47]), "+f"(d[48]), "+f"(d[49]), "+f"(d[50]), "+f"(d[51]), "+f"(d[52]), "+f"(d[53]), "+f"(d[54]), "+f"(d[55]), "+f"(d[56]), "+f"(d[57]), "+f"(d[58]), "+f"(d[59]), "+f"(d[60]), "+f"(d[61]), "+f"(d[62]), "+f"(d[63]), "+f"(d[64]), "+f"(d[65]), "+f"(d[66]), "+f"(d[67]), "+f"(d[68]), "+f"(d[69]), "+f"(d[70]), "+f"(d[71]), "+f"(d[72]), "+f"(d[73]), "+f"(d[74]), "+f"(d[75]), "+f"(d[76]), "+f"(d[77]), "+f"(d[78]), "+f"(d[79]), "+f"(d[80]), "+f"(d[81]), "+f"(d[82]), "+f"(d[83]), "+f"(d[84]), "+f"(d[85]), "+f"(d[86]), "+f"(d[87]), "+f"(d[88]), "+f"(d[89]), "+f"(d[90]), "+f"(d[91]), "+f"(d[92]), "+f"(d[93]), "+f"(d[94]), "+f"(d[95]), "+f"(d[96]), "+f"(d[97]), "+f"(d[98]), "+f"(d[99]), "+f"(d[100]), "+f"(d[101]), "+f"(d[102]), "+f"(d[103]), "+f"(d[104]), "+f"(d[105]), "+f"(d[106]), "+f"(d[107]), "+f"(d[108]), "+f"(d[109]), "+f"(d[110]), "+f"(d[111]), "+f"(d[112]), "+f"(d[113]), "+f"(d[114]), "+f"(d[115]), "+f"(d[116]), "+f"(d[117]), "+f"(d[118]), "+f"(d[119]), "+f"(d[120]), "+f"(d[121]), "+f"(d[122]), "+f"(d[123]), "+f"(d[124]), "+f"(d[125]), "+f"(d[126]), "+f"(d[127])
    : "r"(da), "r"(db), "r"(scale_d));
}

__device__ __forceinline__ void wgmma_ss_n256_tb0(float (&d)[128], uint32_t da, uint32_t db, int scale_d) {
  asm volatile("{\n.reg .pred p;\n.reg .b64 da, db;\nsetp.ne.b32 p, %130, 0;\nmov.b64 da, {%128, 0x40000040};\nmov.b64 db, {%129, 0x40000040};\n"
    "wgmma.mma_async.sync.aligned.m64n256k16.f32.bf16.bf16 {%0, %1, %2, %3, %4, %5, %6, %7, %8, %9, %10, %11, %12, %13, %14, %15, %16, %17, %18, %19, %20, %21, %22, %23, %24, %25, %26, %27, %28, %29, %30, %31, %32, %33, %34, %35, %36, %37, %38, %39, %40, %41, %42, %43, %44, %45, %46, %47, %48, %49, %50, %51, %52, %53, %54, %55, %56, %57, %58, %59, %60, %61, %62, %63, %64, %65, %66, %67, %68, %69, %70, %71, %72, %73, %74, %75, %76, %77, %78, %79, %80, %81, %82, %83, %84, %85, %86, %87, %88, %89, %90, %91, %92, %93, %94, %95, %96, %97, %98, %99, %100, %101, %102, %103, %104, %105, %106, %107, %108, %109, %110, %111, %112, %113, %114, %115, %116, %117, %118, %119, %120, %121, %122, %123, %124, %125, %126, %127}, da, db, p, 1, 1, 0, 0;\n}\n"
    : "+f"(d[0]), "+f"(d[1]), "+f"(d[2]), "+f"(d[3]), "+f"(d[4]), "+f"(d[5]), "+f"(d[6]), "+f"(d[7]), "+f"(d[8]), "+f"(d[9]), "+f"(d[10]), "+f"(d[11]), "+f"(d[12]), "+f"(d[13]), "+f"(d[14]), "+f"(d[15]), "+f"(d[16]), "+f"(d[17]), "+f"(d[18]), "+f"(d[19]), "+f"(d[20]), "+f"(d[21]), "+f"(d[22]), "+f"(d[23]), "+f"(d[24]), "+f"(d[25]), "+f"(d[26]), "+f"(d[27]), "+f"(d[28]), "+f"(d[29]), "+f"(d[30]), "+f"(d[31]), "+f"(d[32]), "+f"(d[33]), "+f"(d[34]), "+f"(d[35]), "+f"(d[36]), "+f"(d[37]), "+f"(d[38]), "+f"(d[39]), "+f"(d[40]), "+f"(d[41]), "+f"(d[42]), "+f"(d[43]), "+f"(d[44]), "+f"(d[45]), "+f"(d[46]), "+f"(d[47]), "+f"(d[48]), "+f"(d[49]), "+f"(d[50]), "+f"(d[51]), "+f"(d[52]), "+f"(d[53]), "+f"(d[54]), "+f"(d[55]), "+f"(d[56]), "+f"(d[57]), "+f"(d[58]), "+f"(d[59]), "+f"(d[60]), "+f"(d[61]), "+f"(d[62]), "+f"(d[63]), "+f"(d[64]), "+f"(d[65]), "+f"(d[66]), "+f"(d[67]), "+f"(d[68]), "+f"(d[69]), "+f"(d[70]), "+f"(d[71]), "+f"(d[72]), "+f"(d[73]), "+f"(d[74]), "+f"(d[75]), "+f"(d[76]), "+f"(d[77]), "+f"(d[78]), "+f"(d[79]), "+f"(d[80]), "+f"(d[81]), "+f"(d[82]), "+f"(d[83]), "+f"(d[84]), "+f"(d[85]), "+f"(d[86]), "+f"(d[87]), "+f"(d[88]), "+f"(d[89]), "+f"(d[90]), "+f"(d[91]), "+f"(d[92]), "+f"(d[93]), "+f"(d[94]), "+f"(d[95]), "+f"(d[96]), "+f"(d[97]), "+f"(d[98]), "+f"(d[99]), "+f"(d[100]), "+f"(d[101]), "+f"(d[102]), "+f"(d[103]), "+f"(d[104]), "+f"(d[105]), "+f"(d[106]), "+f"(d[107]), "+f"(d[108]), "+f"(d[109]), "+f"(d[110]), "+f"(d[111]), "+f"(d[112]), "+f"(d[113]), "+f"(d[114]), "+f"(d[115]), "+f"(d[116]), "+f"(d[117]), "+f"(d[118]), "+f"(d[119]), "+f"(d[120]), "+f"(d[121]), "+f"(d[122]), "+f"(d[123]), "+f"(d[124]), "+f"(d[125]), "+f"(d[126]), "+f"(d[127])
    : "r"(da), "r"(db), "r"(scale_d));
}

__device__ __forceinline__ void wgmma_rs_n256_tb1(float (&d)[128], uint32_t a0, uint32_t a1, uint32_t a2, uint32_t a3, uint32_t db, int scale_d) {
  asm volatile("{\n.reg .pred p;\n.reg .b64 db;\nsetp.ne.b32 p, %133, 0;\nmov.b64 db, {%132, 0x40000040};\n"
    "wgmma.mma_async.sync.aligned.m64n256k16.f32.bf16.bf16 {%0, %1, %2, %3, %4, %5, %6, %7, %8, %9, %10, %11, %12, %13, %14, %15, %16, %17, %18, %19, %20, %21, %22, %23, %24, %25, %26, %27, %28, %29, %30, %31, %32, %33, %34, %35, %36, %37, %38, %39, %40, %41, %42, %43, %44, %45, %46, %47, %48, %49, %50, %51, %52, %53, %54, %55, %56, %57, %58, %59, %60, %61, %62, %63, %64, %65, %66, %67, %68, %69, %70, %71, %72, %73, %74, %75, %76, %77, %78, %79, %80, %81, %82, %83, %84, %85, %86, %87, %88, %89, %90, %91, %92, %93, %94, %95, %96, %97, %98, %99, %100, %101, %102, %103, %104, %105, %106, %107, %108, %109, %110, %111, %112, %113, %114, %115, %116, %117, %118, %119, %120, %121, %122, %123, %124, %125, %126, %127}, {%128, %129, %130, %131}, db, p, 1, 1, 1;\n}\n"
    : "+f"(d[0]), "+f"(d[1]), "+f"(d[2]), "+f"(d[3]), "+f"(d[4]), "+f"(d[5]), "+f"(d[6]), "+f"(d[7]), "+f"(d[8]), "+f"(d[9]), "+f"(d[10]), "+f"(d[11]), "+f"(d[12]), "+f"(d[13]), "+f"(d[14]), "+f"(d[15]), "+f"(d[16]), "+f"(d[17]), "+f"(d[18]), "+f"(d[19]), "+f"(d[20]), "+f"(d[21]), "+f"(d[22]), "+f"(d[23]), "+f"(d[24]), "+f"(d[25]), "+f"(d[26]), "+f"(d[27]), "+f"(d[28]), "+f"(d[29]), "+f"(d[30]), "+f"(d[31]), "+f"(d[32]), "+f"(d[33]), "+f"(d[34]), "+f"(d[35]), "+f"(d[36]), "+f"(d[37]), "+f"(d[38]), "+f"(d[39]), "+f"(d[40]), "+f"(d[41]), "+f"(d[42]), "+f"(d[43]), "+f"(d[44]), "+f"(d[45]), "+f"(d[46]), "+f"(d[47]), "+f"(d[48]), "+f"(d[49]), "+f"(d[50]), "+f"(d[51]), "+f"(d[52]), "+f"(d[53]), "+f"(d[54]), "+f"(d[55]), "+f"(d[56]), "+f"(d[57]), "+f"(d[58]), "+f"(d[59]), "+f"(d[60]), "+f"(d[61]), "+f"(d[62]), "+f"(d[63]), "+f"(d[64]), "+f"(d[65]), "+f"(d[66]), "+f"(d[67]), "+f"(d[68]), "+f"(d[69]), "+f"(d[70]), "+f"(d[71]), "+f"(d[72]), "+f"(d[73]), "+f"(d[74]), "+f"(d[75]), "+f"(d[76]), "+f"(d[77]), "+f"(d[78]), "+f"(d[79]), "+f"(d[80]), "+f"(d[81]), "+f"(d[82]), "+f"(d[83]), "+f"(d[84]), "+f"(d[85]), "+f"(d[86]), "+f"(d[87]), "+f"(d[88]), "+f"(d[89]), "+f"(d[90]), "+f"(d[91]), "+f"(d[92]), "+f"(d[93]), "+f"(d[94]), "+f"(d[95]), "+f"(d[96]), "+f"(d[97]), "+f"(d[98]), "+f"(d[99]), "+f"(d[100]), "+f"(d[101]), "+f"(d[102]), "+f"(d[103]), "+f"(d[104]), "+f"(d[105]), "+f"(d[106]), "+f"(d[107]), "+f"(d[108]), "+f"(d[109]), "+f"(d[110]), "+f"(d[111]), "+f"(d[112]), "+f"(d[113]), "+f"(d[114]), "+f"(d[115]), "+f"(d[116]), "+f"(d[117]), "+f"(d[118]), "+f"(d[119]), "+f"(d[120]), "+f"(d[121]), "+f"(d[122]), "+f"(d[123]), "+f"(d[124]), "+f"(d[125]), "+f"(d[126]), "+f"(d[127])
    : "r"(a0), "r"(a1), "r"(a2), "r"(a3), "r"(db), "r"(scale_d));
}

__device__ __forceinline__ void wgmma_ss_n64_tb0(float (&d)[32], uint32_t da, uint32_t db, int scale_d) {
  asm volatile("{\n.reg .pred p;\n.reg .b64 da, db;\nsetp.ne.b32 p, %34, 0;\nmov.b64 da, {%32, 0x40000040};\nmov.b64 db, {%33, 0x40000040};\n"
    "wgmma.mma_async.sync.aligned.m64n64k16.f32.bf16.bf16 {%0, %1, %2, %3, %4, %5, %6, %7, %8, %9, %10, %11, %12, %13, %14, %15, %16, %17, %18, %19, %20, %21, %22, %23, %24, %25, %26, %27, %28, %29, %30, %31}, da, db, p, 1, 1, 0, 0;\n}\n"
    : "+f"(d[0]), "+f"(d[1]), "+f"(d[2]), "+f"(d[3]), "+f"(d[4]), "+f"(d[5]), "+f"(d[6]), "+f"(d[7]), "+f"(d[8]), "+f"(d[9]), "+f"(d[10]), "+f"(d[11]), "+f"(d[12]), "+f"(d[13]), "+f"(d[14]), "+f"(d[15]), "+f"(d[16]), "+f"(d[17]), "+f"(d[18]), "+f"(d[19]), "+f"(d[20]), "+f"(d[21]), "+f"(d[22]), "+f"(d[23]), "+f"(d[24]), "+f"(d[25]), "+f"(d[26]), "+f"(d[27]), "+f"(d[28]), "+f"(d[29]), "+f"(d[30]), "+f"(d[31])
    : "r"(da), "r"(db), "r"(scale_d));
}

__device__ __forceinline__ void wgmma_rs_n64_tb0(float (&d)[32], uint32_t a0, uint32_t a1, uint32_t a2, uint32_t a3, uint32_t db, int scale_d) {
  asm volatile("{\n.reg .pred p;\n.reg .b64 db;\nsetp.ne.b32 p, %37, 0;\nmov.b64 db, {%36, 0x40000040};\n"
    "wgmma.mma_async.sync.aligned.m64n64k16.f32.bf16.bf16 {%0, %1, %2, %3, %4, %5, %6, %7, %8, %9, %10, %11, %12, %13, %14, %15, %16, %17, %18, %19, %20, %21, %22, %23, %24, %25, %26, %27, %28, %29, %30, %31}, {%32, %33, %34, %35}, db, p, 1, 1, 0;\n}\n"
    : "+f"(d[0]), "+f"(d[1]), "+f"(d[2]), "+f"(d[3]), "+f"(d[4]), "+f"(d[5]), "+f"(d[6]), "+f"(d[7]), "+f"(d[8]), "+f"(d[9]), "+f"(d[10]), "+f"(d[11]), "+f"(d[12]), "+f"(d[13]), "+f"(d[14]), "+f"(d[15]), "+f"(d[16]), "+f"(d[17]), "+f"(d[18]), "+f"(d[19]), "+f"(d[20]), "+f"(d[21]), "+f"(d[22]), "+f"(d[23]), "+f"(d[24]), "+f"(d[25]), "+f"(d[26]), "+f"(d[27]), "+f"(d[28]), "+f"(d[29]), "+f"(d[30]), "+f"(d[31])
    : "r"(a0), "r"(a1), "r"(a2), "r"(a3), "r"(db), "r"(scale_d));
}

__device__ __forceinline__ void wgmma_ss_n32_tb0(float (&d)[16], uint32_t da, uint32_t db, int scale_d) {
  asm volatile("{\n.reg .pred p;\n.reg .b64 da, db;\nsetp.ne.b32 p, %18, 0;\nmov.b64 da, {%16, 0x40000040};\nmov.b64 db, {%17, 0x40000040};\n"
    "wgmma.mma_async.sync.aligned.m64n32k16.f32.bf16.bf16 {%0, %1, %2, %3, %4, %5, %6, %7, %8, %9, %10, %11, %12, %13, %14, %15}, da, db, p, 1, 1, 0, 0;\n}\n"
    : "+f"(d[0]), "+f"(d[1]), "+f"(d[2]), "+f"(d[3]), "+f"(d[4]), "+f"(d[5]), "+f"(d[6]), "+f"(d[7]), "+f"(d[8]), "+f"(d[9]), "+f"(d[10]), "+f"(d[11]), "+f"(d[12]), "+f"(d[13]), "+f"(d[14]), "+f"(d[15])
    : "r"(da), "r"(db), "r"(scale_d));
}

__device__ __forceinline__ void wgmma_rs_n32_tb0(float (&d)[16], uint32_t a0, uint32_t a1, uint32_t a2, uint32_t a3, uint32_t db, int scale_d) {
  asm volatile("{\n.reg .pred p;\n.reg .b64 db;\nsetp.ne.b32 p, %21, 0;\nmov.b64 db, {%20, 0x40000040};\n"
    "wgmma.mma_async.sync.aligned.m64n32k16.f32.bf16.bf16 {%0, %1, %2, %3, %4, %5, %6, %7, %8, %9, %10, %11, %12, %13, %14, %15}, {%16, %17, %18, %19}, db, p, 1, 1, 0;\n}\n"
    : "+f"(d[0]), "+f"(d[1]), "+f"(d[2]), "+f"(d[3]), "+f"(d[4]), "+f"(d[5]), "+f"(d[6]), "+f"(d[7]), "+f"(d[8]), "+f"(d[9]), "+f"(d[10]), "+f"(d[11]), "+f"(d[12]), "+f"(d[13]), "+f"(d[14]), "+f"(d[15])
    : "r"(a0), "r"(a1), "r"(a2), "r"(a3), "r"(db), "r"(scale_d));
}

struct Ctx {
  uint32_t sb;
  uint32_t pdelta;
  uint32_t fb, ph;
  __device__ __forceinline__ uint32_t slot(uint32_t n) const { return sb + (n % NS) * SLOT; }
  __device__ __forceinline__ uint32_t full(uint32_t n, uint32_t w) const { return sb + OFF_BAR + 40 * w + 8 * (n % NS); }
  __device__ __forceinline__ uint32_t empty(uint32_t n) const { return sb + OFF_BAR + 80 + 8 * (n % NS); }
  __device__ __forceinline__ uint32_t afull(int h) const { return sb + OFF_BAR + 120 + 8 * h; }
  __device__ __forceinline__ uint32_t afree(int h) const { return sb + OFF_BAR + 136 + 8 * h; }
  __device__ __forceinline__ uint32_t gbar() const { return sb + OFF_BAR + 152; }
  __device__ __forceinline__ uint32_t dbar() const { return sb + OFF_BAR + 160; }
  __device__ __forceinline__ uint32_t xbar() const { return sb + OFF_BAR + 168; }
  __device__ __forceinline__ uint32_t sbar(int w) const { return sb + OFF_BAR + 176 + 8 * w; }
  __device__ __forceinline__ void wait_full(uint32_t n) {
    const uint32_t s = n % NS;
    mbar_wait(fb + 8 * s, (ph >> s) & 1);
    ph ^= 1u << s;
  }
  __device__ __forceinline__ uint32_t cbar() const { return sb + OFF_BAR + 192; }
  __device__ __forceinline__ uint32_t fbar(int i) const { return sb + OFF_BAR + 200 + 8 * i; }
  template <int LO = N_ATT0 - NS> __device__ __forceinline__ void release(uint32_t n) const {
    if ((threadIdx.x & 31) == 0) { uint32_t e = empty(n); mbar_arrive(e); mbar_arrive_cluster(e + (RELALL || n - LO < N_FIN0 - N_ATT0 ? pdelta : 0)); }
  }
};

template <int TB, int LO, class Pre, class Post>
__device__ __forceinline__ void gemm8(Ctx& cx, float (&acc)[128], uint32_t n0, uint32_t nstep, Pre pre, Post post) {
  zero_regs(acc);
#pragma unroll 1
  for (int kb = 0; kb < 8; kb++) {
    uint32_t n = n0 + kb * nstep;
    pre(kb);
    cx.wait_full(n);
    if (n < 48) STAMP(340 + n);
    uint32_t da = desc_k(cx.sb + OFF_Q + kb * CH);
    uint32_t db = TB ? desc_mn(cx.slot(n)) : desc_k(cx.slot(n));
    wg_fence();
#pragma unroll
    for (int k = 0; k < 4; k++) {
      if (TB) wgmma_ss_n256_tb1(acc, da + k * 2, db + k * 128, 1);
      else wgmma_ss_n256_tb0(acc, da + k * 2, db + k * 2, 1);
    }
    wg_commit();
    if (kb > 0) { wg_wait<1>(); cx.release<LO>(n - nstep); post(kb - 1); }
  }
  wg_wait<0>();
  fence_regs(acc);
  cx.release<LO>(n0 + 7 * nstep);
  post(7);
}

__device__ __forceinline__ int sigma(int r) { return (r & ~30) | ((r & 6) << 2) | ((r & 24) >> 2); }

__global__ void __cluster_dims__(2, 1, 1) __launch_bounds__(384, 1)
bf_kernel(const __grid_constant__ Maps maps, const __grid_constant__ Ptrs wp, const __nv_bfloat16* __restrict__ x,
          const __nv_bfloat16* __restrict__ dw, __nv_bfloat16* __restrict__ out, int mode) {
  extern __shared__ __align__(1024) uint8_t smem_raw[];
  Ctx cx;
  cx.sb = smem_u32(smem_raw);
  const uint32_t sb = cx.sb;
  const int tid = threadIdx.x, lane = tid & 31, warp = __shfl_sync(~0u, tid >> 5, 0);
  const uint32_t rank = cluster_rank();
  cx.pdelta = mapa(sb, rank ^ 1) - sb;
  const int cid = blockIdx.x >> 1;
  const bool spare = cid < 2;
  const int pairi = cid - 2, batch = pairi >> 5, pp = pairi & 31;
  const int row0 = 125 * pp - 1 + 64 * (int)rank;
  if (tid == 0) {
    mbar_init(cx.xbar(), 1);
    asm volatile("fence.mbarrier_init.release.cluster;" ::: "memory");
    if (!spare) {
      mbar_expect_tx(cx.xbar(), TILE);
      tma4d(sb + OFF_Q, &maps.x, row0, 0, batch, cx.xbar());
      tma4d(sb + OFF_Q + SLOT, &maps.x, row0, 4, batch, cx.xbar());
    }
    if (sb & 1023) TRAP(sb, 12345);
  } else if (tid == 32) {
#pragma unroll 1
    for (int i = 0; i < (int)NS; i++) { mbar_init(cx.full(i, 0), 1); mbar_init(cx.full(i, 1), 1); mbar_init(cx.empty(i), 8); }
    mbar_init(cx.afull(0), 1); mbar_init(cx.afull(1), 1);
    mbar_init(cx.afree(0), spare ? 4 : 8); mbar_init(cx.afree(1), 4);
    mbar_init(cx.gbar(), 2); mbar_init(cx.dbar(), 8); mbar_init(cx.cbar(), 2);
    mbar_init(cx.sbar(0), spare ? 4 : 8); mbar_init(cx.sbar(1), spare ? 4 : 8);
#pragma unroll 1
    for (int i = 0; i < 6; i++) mbar_init(cx.fbar(i), 1);
    asm volatile("fence.mbarrier_init.release.cluster;" ::: "memory");
  } else if (tid == 64) {
    if (!spare && mode != 2) {
      const int i = blockIdx.x - 4;
      l2_prefetch((i & 1 ? wp.wq : wp.wk) + (i >> 1) * 8192, 8192);
    }
    if (!spare && mode != 1) l2_prefetch(wp.wup + (blockIdx.x - 4) * 8192, 8192);
    map_prefetch(spare ? &maps.k : &maps.up);
    map_prefetch(spare ? &maps.q : &maps.xs);
    map_prefetch(&maps.xl);
  }
  __syncthreads();
  cluster_arrive();

  if (__builtin_expect(warp >= 8, 1)) {
    reg_dealloc<PREG>();
    cluster_wait();
    const uint32_t ro = rank * 16384;
    if (warp == 8) {
      uint32_t si = 0, par = 1, pn = 0;
      auto step = [&](uint32_t w, auto issue) {
        mbar_wait(sb + OFF_BAR + 80 + 8 * si, par);
        const uint32_t fb = sb + OFF_BAR + 40 * w + 8 * si, s = sb + si * SLOT;
        if (elect_one()) { PSTAMP(0, pn); mbar_expect_tx(fb, SLOT); issue(s, fb); PSTAMP(1, pn); }
        pn++;
        if (++si == NS) { si = 0; par ^= 1; }
      };
      if (spare) {
        if (mode != 2) {
#pragma unroll 1
          for (uint32_t n = 0; n < 128; n++) {
            const uint32_t w = (n >> 3) & 1, kb = n & 7, j = n >> 4;
            const CUtensorMap* m = j < 2 ? &maps.k : ((j == 2 || j == 4) ? &maps.ao : &maps.mg);
            const int c1 = j < 2 ? 256 * w + 128 * rank : 64 * kb + (j >= 6 ? 512 : 0), c2 = j < 2 ? kb : 4 * w + 2 * rank;
            step(w, [&](uint32_t s, uint32_t fb) { tma3d_mc(s + ro, m, c1, c2, fb); });
          }
        }
      } else if (mode != 1) {
#pragma unroll 1
        for (uint32_t n = 0; n < 32; n++) {
          const uint32_t w = (n >> 3) & 1;
          step(w, [&](uint32_t s, uint32_t fb) { tma3d(s, &maps.up, 64 * (n & 7), (n < 16 ? 8 : 0) + 4 * w, fb); });
        }
#pragma unroll 1
        for (uint32_t n = 0; n < 16; n++) {
          const uint32_t w = n >> 3, kb = n & 7;
          if ((n & 3) == 0) mbar_wait(cx.fbar(n >> 2), 0);
          step(w, [&](uint32_t s, uint32_t fb) { bulk_g2s(s, g_wqk + kb * TILE + w * SLOT, SLOT, fb); });
        }
        mbar_wait(cx.fbar(4), 0);
#pragma unroll 1
        for (uint32_t i = 0; i < 2 * NTILE; i++) {
          const uint32_t t = i >> 1;
          step(t & 1, [&](uint32_t s, uint32_t fb) { tma4d_mc(s + ro, &maps.xl, 64 * t, 4 * ((t ^ i) & 1) + 2 * rank, batch, fb); });
        }
        mbar_wait(cx.fbar(5), 0);
#pragma unroll 1
        for (uint32_t n = 0; n < 32; n++) {
          const uint32_t i = n >> 1, w = n & 1;
          step(w, [&](uint32_t s, uint32_t fb) { bulk_g2s(s, g_wf + (i < 8 ? i : 8 + ((i + 4 * w) & 7)) * TILE + w * SLOT, SLOT, fb); });
        }
      }
    } else if (warp == 10) {
      if (lane == 0) {
        if (!spare && mode != 1) {
          const uint32_t ep1 = ld_relaxed(&g_flags[F_DONE * 32]) / NCTA + 1;
#pragma unroll 1
          for (int i = 0; i < 6; i++) {
            wait_flag(i < 4 ? F_WQK + 2 * (i & 1) + (i >> 1) : (i == 4 ? F_XA + batch : F_WF), ep1 * (i < 4 ? 4 : (i == 4 ? 64 : 32)));
            mbar_arrive(cx.fbar(i));
          }
        }
        mbar_wait(cx.dbar(), 0);
      }
    } else if (spare) {
      if (lane == 0 && mode != 2) {
        if (warp == 9) {
          const int s = 2 * cid + rank;
#pragma unroll 1
          for (int rh = 0; rh < 12; rh++) {
            const int r = rh >> 1, h = rh & 1;
            const CUtensorMap* m = r < 2 ? &maps.q : (r < 4 ? &maps.v : &maps.dn);
            const int row = 64 * (s + 4 * (r & 1));
            if (r > 0) mbar_wait(cx.afree(h), (r - 1) & 1);
            mbar_expect_tx(cx.afull(h), SLOT);
            tma3d(sb + OFF_Q + h * SLOT, m, row, 4 * h, cx.afull(h));
            tma3d(sb + OFF_Q + h * SLOT + 16384, m, row, 4 * h + 2, cx.afull(h));
          }
        } else {
#pragma unroll 1
          for (int e = 0; e < 12; e++) {
            mbar_wait(cx.sbar(e & 1), (e >> 1) & 1);
            signal_flag(e < 4 ? F_WQK + e : F_WF);
          }
        }
      }
    } else {
      if (warp == 11) {
        bar_sync_n(3, 288);
        if (lane == 0 && mode != 2) {
#pragma unroll 1
          for (int i = 0; i < 8; i++) {
            tma4d_store(&maps.xs, sb + OFF_Q + i * CH, row0 + 1, i, batch);
            asm volatile("cp.async.bulk.commit_group;" ::: "memory");
            __nanosleep(XPACE);
          }
          const int i = blockIdx.x - 4;
          l2_prefetch(wp.wv + i * 4096, 4096); l2_prefetch(wp.wao + i * 4096, 4096);
          l2_prefetch(wp.wmg + i * 8192, 8192); l2_prefetch(wp.wdn + i * 4096, 4096);
          asm volatile("cp.async.bulk.wait_group 0;" ::: "memory");
          signal_flag(F_XA + batch);
        }
        if (lane == 0 && mode != 1) {
          mbar_wait(cx.sbar(0), 0);
          fence_gpu();
          mbar_arrive(cx.gbar());
          mbar_arrive_cluster(cx.gbar() + cx.pdelta);
        }
        __syncwarp();
      }
      if (mode != 1) {
        const int ch = 4 * (warp >> 1 & 1) + (lane >> 3), lu = lane & 7;
        uint32_t dk[3][4];
#pragma unroll
        for (int k = 0; k < 3; k++)
#pragma unroll
          for (int jj = 0; jj < 4; jj++) dk[k][jj] = __ldg((const uint32_t*)dw + 256 * k + 32 * ch + 16 * (lu >> 2) + 4 * jj + (lu & 3));
        mbar_wait_cl(cx.gbar(), 0);
        mbar_wait(cx.sbar(1), 0);
        uint8_t* up_ = g_uc + (size_t)(2 * pairi) * TILE + ch * CH;
        const float4* sp_ = (const float4*)g_st + pairi * 128;
        uint32_t p1[4] = {0, 0, 0, 0}, p2[4] = {0, 0, 0, 0};
        uint32_t oo = 0;
#pragma unroll 1
        for (int L = 64 * (int)rank - 1; L <= 64 * (int)rank + (NOCONV ? -2 : 64); L++) {
          const uint32_t Lc = min(max(L, 0), 127), oc = (Lc >> 6) * TILE + (Lc & 63) * 128 + ((lu ^ (Lc & 7)) << 4);
          const uint4 g = __ldcg((const uint4*)(up_ + 128 * TILE + oc));
          const float4 st = __ldcg(sp_ + Lc);
          uint4* uo = (uint4*)(up_ + oo);
          const uint4 u = __ldcg(uo);
          oo = oc;
          const float mu_ = (st.x + st.z) * (1.f / DD);
          const float r = rsqrtf(fmaxf(fmaf(-mu_, mu_, (st.y + st.w) * (1.f / DD)), 0.f) + 1e-5f), m = -mu_ * r;
          const uint32_t gg[4] = {g.x, g.y, g.z, g.w}, uu[4] = {u.x, u.y, u.z, u.w};
          uint32_t o[4];
#pragma unroll
          for (int jj = 0; jj < 4; jj++) {
            const uint32_t gn = pack2(fmaf(blo(gg[jj]), r, m), fmaf(bhi(gg[jj]), r, m));
            o[jj] = hmul2(uu[jj], hfma2(gn, dk[2][jj], p1[jj]));
            p1[jj] = hfma2(gn, dk[1][jj], p2[jj]);
            p2[jj] = hmul2(gn, dk[0][jj]);
          }
          if (L > 64 * (int)rank) __stcg(uo, make_uint4(o[0], o[1], o[2], o[3]));
        }
        __syncwarp();
        if (lane == 0) mbar_arrive(cx.cbar());
        if (lane == 0 && warp == 9) {
          const uint8_t* uc = g_uc + (size_t)(2 * pairi + rank) * TILE;
          mbar_wait(cx.cbar(), 0);
#pragma unroll 1
          for (int h = 0; h < 2; h++) {
            mbar_wait(cx.afree(h), 0);
            if (h == 0) {
              const int r0 = max(row0, 0), r1 = min(row0 + 64, TT);
              l2_prefetch(x + ((size_t)batch * TT + r0) * DD, (r1 - r0) * DD * 2);
            }
            fence_async_all();
            mbar_expect_tx(cx.afull(h), h ? CH : 7 * CH);
            bulk_g2s(sb + OFF_Q + h * 7 * CH, uc + h * 7 * CH, h ? CH : 7 * CH, cx.afull(h));
          }
        }
      }
    }
    __syncwarp();
    cluster_arrive();
    cluster_wait();
  } else {
    reg_alloc<CREG>();
    STAMP(0); GSTAMP(500);
    const int w = warp >> 2, wq = warp & 3, q = lane >> 2, c = lane & 3;
    cx.fb = cx.full(0, w); cx.ph = 0;
    const int rlo = 16 * wq + q;
    const int mrow = 16 * wq + (lane & 15);
    const uint32_t moff = mrow * 128, mx = mrow & 7, mu = lane >> 4;
    float acc[128];

    if (spare) {
      cluster_wait();
      if (mode != 2) {
        const int s = 2 * cid + rank;
        int ar = 0;
#pragma unroll 1
        for (int j = 0; j < 8; j++) {
          MARK(mode * 1000 + j * 10); STAMP(1 + 2 * j);
          const bool tmaA = (j != 3 && j != 5), t1 = (j == 2 || j == 4), nextTma = (j != 2 && j != 4 && j != 7);
          auto pre = [&](int kb) {
            if (tmaA && (kb & 3) == 0) mbar_wait(cx.afull(kb >> 2), ar & 1);
            if (!tmaA && kb == (w ? 0 : 4)) bar_sync(w ? 5 : 6);
          };
          auto post = [&](int kb) {
            if (w == 1 && (kb & 3) == 3) {
              if (nextTma) { if (lane == 0) mbar_arrive(cx.afree(kb >> 2)); }
              else if (t1 && kb == 3) bar_arrive(4);
            }
          };
          if (j < 2) gemm8<0, 0>(cx, acc, 16 * j + 8 * w, 1, pre, post);
          else gemm8<1, 0>(cx, acc, 16 * j + 8 * w, 1, pre, post);
          MARK(mode * 1000 + j * 10 + 1); STAMP(2 + 2 * j);
          if (tmaA) ar++;
          const float sc = j < 2 ? 0.04419417382415922f * 1.4426950408889634f : 1.f;
          uint32_t pk[64];
#pragma unroll
          for (int i = 0; i < 64; i++) pk[i] = pack2(acc[2 * i] * sc, acc[2 * i + 1] * sc);
          if (t1) {
            if (w == 0) bar_sync(4);
#pragma unroll
            for (int ks = 0; ks < 16; ks++)
              stsm4(sb + OFF_Q + (4 * w + (ks >> 2)) * CH + moff + (((2 * (ks & 3) + mu) ^ mx) << 4), pk[4 * ks], pk[4 * ks + 1], pk[4 * ks + 2], pk[4 * ks + 3]);
            fence_async_smem();
            bar_arrive(w ? 6 : 5);
          } else {
            const int blk = s + 4 * (j < 2 ? j : (j < 6 ? (j >> 2) : (j & 1)));
            uint8_t* dst = (j < 2 ? g_wqk + blk * TILE : g_wf + (j < 6 ? 8 + blk : blk) * TILE) + 4 * w * CH;
            const int r0 = j >= 6 ? sigma(rlo) : rlo, r1 = j >= 6 ? sigma(rlo + 8) : rlo + 8;
            uint8_t* d0 = dst + r0 * 128, * d1 = dst + r1 * 128;
#pragma unroll
            for (int i = 0; i < 8; i++) {
              const int u = 4 * (i & 1) + c;
              *(uint4*)(d0 + (i >> 1) * CH + ((u ^ (r0 & 7)) << 4)) = make_uint4(pk[8 * i], pk[8 * i + 2], pk[8 * i + 4], pk[8 * i + 6]);
              *(uint4*)(d1 + (i >> 1) * CH + ((u ^ (r1 & 7)) << 4)) = make_uint4(pk[8 * i + 1], pk[8 * i + 3], pk[8 * i + 5], pk[8 * i + 7]);
            }
            __syncwarp();
            if (lane == 0) mbar_arrive(cx.sbar(w));
          }
        }
      }
    } else {
      {
        const uint32_t r = 8 * warp + (lane & 7);
        const uint32_t rb = sb + OFF_Q + r * 128 + ((lane & 7) << 4), base = rb + (lane >> 3) * 2 * CH;
        mbar_wait(cx.xbar(), 0);
        STAMP(300);
        uint32_t x0;
        asm volatile("ld.shared.b32 %0, [%1];" : "=r"(x0) : "r"(rb) : "memory");
        const float sh = blo(x0);
        float s1 = 0.f, s2 = 0.f, t1 = 0.f, t2 = 0.f;
#pragma unroll 1
        for (int o = 0; o < 4; o++) {
          const uint32_t a = (base ^ ((o & 1) << 6)) + (o >> 1) * CH;
#pragma unroll
          for (int i = 0; i < 4; i++) {
            uint32_t v[4];
            lds128(a ^ (i << 4), v);
#pragma unroll
            for (int k = 0; k < 4; k++) {
              const float d = blo(v[k]) - sh, e = bhi(v[k]) - sh;
              s1 += d; s2 = fmaf(d, d, s2); t1 += e; t2 = fmaf(e, e, t2);
            }
          }
        }
        s1 += t1; s2 += t2;
        s1 += __shfl_xor_sync(~0u, s1, 8); s2 += __shfl_xor_sync(~0u, s2, 8);
        s1 += __shfl_xor_sync(~0u, s1, 16); s2 += __shfl_xor_sync(~0u, s2, 16);
        s1 *= (1.f / DD);
        const float rs = rsqrtf(fmaxf(fmaf(-s1, s1, s2 * (1.f / DD)), 0.f) + 1e-5f), mr = -(sh + s1) * rs;
        STAMP(301);
#pragma unroll 1
        for (int o = 0; o < 4; o++) {
          const uint32_t a = (base ^ ((o & 1) << 6)) + (o >> 1) * CH;
#pragma unroll
          for (int i = 0; i < 4; i++) {
            uint32_t v[4];
            lds128(a ^ (i << 4), v);
#pragma unroll
            for (int k = 0; k < 4; k++) v[k] = pack2(fmaf(blo(v[k]), rs, mr), fmaf(bhi(v[k]), rs, mr));
            sts128(a ^ (i << 4), v[0], v[1], v[2], v[3]);
          }
        }
        STAMP(302);
        fence_async_smem();
      }
      cluster_wait();
      MARK(510); STAMP(1);
      bar_sync_n(3, 288);
      if (mode != 1) {
        MARK(511); STAMP(2);
        uint32_t qf[16];
#pragma unroll 1
        for (int ph = 0; ph < 3; ph++) {
          gemm8<1, N_ATT0 - NS>(cx, acc, 16 * ph + 8 * w, 1, [](int) {}, [&](int kb) { if (ph == 2 && w == 1 && kb == 3) bar_arrive(4); });
          MARK(512 + 2 * ph); STAMP(3 + 2 * ph);
          if (ph < 2) {
            float s1a = 0.f, s2a = 0.f, s1b = 0.f, s2b = 0.f;
            uint8_t* d = g_uc + (size_t)(2 * pairi + rank + (ph ? 0 : 128)) * TILE + 4 * w * CH + rlo * 128;
#pragma unroll
            for (int i = 0; i < 8; i++) {
              uint32_t pa[4], pb[4];
#pragma unroll
              for (int jj = 0; jj < 4; jj++) {
                const int j = 4 * i + jj;
                const float a0 = gelu(acc[4 * j]), a1 = gelu(acc[4 * j + 1]), b0 = gelu(acc[4 * j + 2]), b1 = gelu(acc[4 * j + 3]);
                s1a += a0 + a1; s2a = fmaf(a0, a0, s2a); s2a = fmaf(a1, a1, s2a);
                s1b += b0 + b1; s2b = fmaf(b0, b0, s2b); s2b = fmaf(b1, b1, s2b);
                pa[jj] = pack2(a0, a1); pb[jj] = pack2(b0, b1);
              }
              uint8_t* e = d + (i >> 1) * CH + (((4 * (i & 1) + c) ^ q) << 4);
              STG((uint4*)e, make_uint4(pa[0], pa[1], pa[2], pa[3]));
              STG((uint4*)(e + 1024), make_uint4(pb[0], pb[1], pb[2], pb[3]));
            }
            STAMP(310 + ph);
            if (ph == 0) {
#pragma unroll
              for (int o = 1; o < 4; o <<= 1) {
                s1a += __shfl_xor_sync(~0u, s1a, o); s2a += __shfl_xor_sync(~0u, s2a, o);
                s1b += __shfl_xor_sync(~0u, s1b, o); s2b += __shfl_xor_sync(~0u, s2b, o);
              }
              float2* sp = g_st + ((2 * pairi + rank) * 64 + rlo) * 2 + w;
              if (c == 0) { __stcg(sp, make_float2(s1a, s2a)); __stcg(sp + 16, make_float2(s1b, s2b)); }
            }
            __syncwarp();
            if (lane == 0) mbar_arrive(cx.sbar(ph));
          } else {
            mbar_wait(cx.gbar(), 0);
            if (w == 0) bar_sync(4);
#pragma unroll
            for (int i = 0; i < 8; i++) {
              const uint32_t a = sb + OFF_Q + (4 * w + (i >> 1)) * CH + rlo * 128 + (((4 * (i & 1) + c) ^ q) << 4);
              sts128(a, pack2(acc[16 * i], acc[16 * i + 1]), pack2(acc[16 * i + 4], acc[16 * i + 5]), pack2(acc[16 * i + 8], acc[16 * i + 9]), pack2(acc[16 * i + 12], acc[16 * i + 13]));
              sts128(a + 1024, pack2(acc[16 * i + 2], acc[16 * i + 3]), pack2(acc[16 * i + 6], acc[16 * i + 7]), pack2(acc[16 * i + 10], acc[16 * i + 11]), pack2(acc[16 * i + 14], acc[16 * i + 15]));
            }
            fence_async_smem();
            bar_sync_n(12 + w, 128);
          }
          MARK(513 + 2 * ph); STAMP(4 + 2 * ph);
        }
        if (w == 1) {
#pragma unroll
          for (int ks = 0; ks < 4; ks++) ldsm4(sb + OFF_P + moff + (((2 * ks + mu) ^ mx) << 4), qf[4 * ks], qf[4 * ks + 1], qf[4 * ks + 2], qf[4 * ks + 3]);
        }
        bar_arrive(w ? 6 : 5);

        float m0 = -INFINITY, m1 = -INFINITY, l0 = 0.f, l1 = 0.f;
        const uint32_t exa = sb + OFF_EX + (tid & 127) * 16;
        const uint32_t dq = desc_k(sb + OFF_Q), dp = desc_k(sb + OFF_P);
        const uint32_t pw = sb + OFF_P + moff;
        float S[32];
        uint32_t P[16];
        float f0, f1, i0, i1;
        zero_regs(acc);
        auto rescale = [&]() {
#pragma unroll
          for (int j = 0; j < 32; j++) { acc[4 * j] *= f0; acc[4 * j + 1] *= f0; acc[4 * j + 2] *= f1; acc[4 * j + 3] *= f1; }
        };
        auto recv_px = [&](uint32_t n, bool live, int kmax) {
          bar_sync(2 - w);
          float a, b;
          asm volatile("ld.shared.v4.f32 {%0, %1, %2, %3}, [%4];" : "=f"(a), "=f"(b), "=f"(l0), "=f"(l1) : "r"(exa) : "memory");
          if (__builtin_expect(live && __any_sync(~0u, a != m0 || b != m1), 0)) { f0 = ex2(m0 - a); f1 = ex2(m1 - b); rescale(); }
          m0 = a; m1 = b;
          const uint32_t db = desc_mn(cx.slot(n));
          wg_fence();
#pragma unroll
          for (int k = 0; k < 4; k++) if (k < kmax) wgmma_ss_n256_tb1(acc, dp + k * 2, db + k * 128, 1);
        };
        auto qk_lo = [&](uint32_t n, int k0, int k1) {
          const uint32_t dk = desc_k(cx.slot(n));
          wg_fence();
#pragma unroll
          for (int k = 0; k < 16; k++)
            if (k >= k0 && k < k1) wgmma_ss_n64_tb0(S, dq + (k >> 2) * 512 + (k & 3) * 2, dk + (k >> 2) * 512 + (k & 3) * 2, 1);
          wg_commit();
        };
        auto qk_hi = [&](uint32_t n, int k0, int k1) {
          const uint32_t dk = desc_k(cx.slot(n));
          wg_fence();
#pragma unroll
          for (int k = 0; k < 12; k++)
            if (k >= k0 && k < k1) wgmma_ss_n64_tb0(S, dq + 2048 + (k >> 2) * 512 + (k & 3) * 2, dk + (k >> 2) * 512 + (k & 3) * 2, 1);
#pragma unroll
          for (int k = 0; k < 4; k++)
            if (k1 == 16) wgmma_rs_n64_tb0(S, qf[4 * k], qf[4 * k + 1], qf[4 * k + 2], qf[4 * k + 3], dk + 1536 + k * 2, 1);
          wg_commit();
        };
        auto expsum = [&](float d0, float d1, float& s0, float& s1, bool sub, int j0, int j1) {
#pragma unroll
          for (int j = j0; j < j1; j++) {
            float a0 = ex2(sub ? S[4 * j] - d0 : S[4 * j]), a1 = ex2(sub ? S[4 * j + 1] - d0 : S[4 * j + 1]);
            float b0 = ex2(sub ? S[4 * j + 2] - d1 : S[4 * j + 2]), b1 = ex2(sub ? S[4 * j + 3] - d1 : S[4 * j + 3]);
            s0 += a0 + a1; s1 += b0 + b1;
            P[2 * j] = pack2(a0, a1); P[2 * j + 1] = pack2(b0, b1);
          }
        };
        auto softmax = [&](auto mid) -> bool {
          float s0 = 0.f, s1 = 0.f;
          expsum(0.f, 0.f, s0, s1, false, 0, MIDJ);
#pragma unroll
          for (int i = 0; i < 2 * MIDJ; i++) asm volatile("" : "+r"(P[i]));
          mid();
#pragma unroll
          for (int i = 4 * MIDJ; i < 32; i++) asm volatile("" : "+f"(S[i]));
          expsum(0.f, 0.f, s0, s1, false, MIDJ, 8);
          float x0 = fmaxf(S[0], S[1]), x1 = fmaxf(S[2], S[3]);
#pragma unroll
          for (int j = 1; j < 8; j++) { x0 = fmaxf(x0, fmaxf(S[4 * j], S[4 * j + 1])); x1 = fmaxf(x1, fmaxf(S[4 * j + 2], S[4 * j + 3])); }
          x0 = fmaxf(x0, __shfl_xor_sync(~0u, x0, 1)); x1 = fmaxf(x1, __shfl_xor_sync(~0u, x1, 1));
          x0 = fmaxf(x0, __shfl_xor_sync(~0u, x0, 2)); x1 = fmaxf(x1, __shfl_xor_sync(~0u, x1, 2));
          bool chg = false;
          if (__builtin_expect(__any_sync(~0u, x0 > LAZY || x1 > LAZY || m0 != i0 || m1 != i1), 0)) {
            x0 += i0; x1 += i1;
            chg = __any_sync(~0u, x0 > m0 + LAZY || x1 > m1 + LAZY);
            if (chg) {
              x0 = fmaxf(x0, m0); x1 = fmaxf(x1, m1);
              f0 = ex2(m0 - x0); f1 = ex2(m1 - x1);
              m0 = x0; m1 = x1;
              l0 *= f0; l1 *= f1;
            }
            s0 = 0.f; s1 = 0.f;
            expsum(m0 - i0, m1 - i1, s0, s1, true, 0, 8);
          }
          l0 += s0; l1 += s1;
          return chg;
        };
        auto sinit = [&](bool first) {
          i0 = first ? 0.f : m0; i1 = first ? 0.f : m1;
#pragma unroll
          for (int j = 0; j < 8; j++) { S[4 * j] = -i0; S[4 * j + 1] = -i0; S[4 * j + 2] = -i1; S[4 * j + 3] = -i1; }
          fence_regs(S);
        };
        auto send = [&]() {
#pragma unroll
          for (int ks = 0; ks < 4; ks++) stsm4(pw + (((2 * ks + mu) ^ mx) << 4), P[4 * ks], P[4 * ks + 1], P[4 * ks + 2], P[4 * ks + 3]);
          asm volatile("st.shared.v4.f32 [%0], {%1, %2, %3, %4};" :: "r"(exa), "f"(m0), "f"(m1), "f"(l0), "f"(l1) : "memory");
          fence_async_smem();
          bar_arrive(1 + w);
        };
        auto po = [&](uint32_t n) {
          const uint32_t db = desc_mn(cx.slot(n));
          wg_fence();
#pragma unroll
          for (int k = 0; k < 4; k++) wgmma_rs_n256_tb1(acc, P[4 * k], P[4 * k + 1], P[4 * k + 2], P[4 * k + 3], db + k * 128, 1);
          wg_commit();
        };
        if (w == 1) bar_sync(5);
#pragma unroll 1
        for (int t = w; t < NTILE; t += 2) {
          const uint32_t n = N_ATT0 + 2 * t;
          MARK(600 + t); FSTAMP(32 + (t >> 1) * 8);
          sinit(t < 2);
          cx.wait_full(n);
          {
            const uint32_t da = dq + w * 2048, dk = desc_k(cx.slot(n));
            wg_fence();
#pragma unroll
            for (int k = 0; k < QKA; k++) wgmma_ss_n64_tb0(S, da + (k >> 2) * 512 + (k & 3) * 2, dk + (k >> 2) * 512 + (k & 3) * 2, 1);
            wg_commit();
          }
          wg_wait<1>();
          fence_regs(acc);
          fence_regs(P);
          if (t >= 2) cx.release(n - 4);
          if (w == 0) qk_lo(n, QKA, 16); else qk_hi(n, QKA, 16);
          if (t == 0) {
            bar_sync(6);
#pragma unroll
            for (int ks = 0; ks < 4; ks++) ldsm4(pw + (((2 * ks + mu) ^ mx) << 4), qf[4 * ks], qf[4 * ks + 1], qf[4 * ks + 2], qf[4 * ks + 3]);
          }
          FSTAMP(33 + (t >> 1) * 8);
          cx.wait_full(n + 1);
          if (w == 0) qk_hi(n + 1, 0, 16); else qk_lo(n + 1, 0, 16);
          FSTAMP(34 + (t >> 1) * 8);
          if (t > 0) {
            recv_px(n - 1, t > 1, PXS);
            wg_commit();
            wg_wait<1>();
          } else {
            wg_wait<0>();
          }
          fence_regs(S);
          FSTAMP(35 + (t >> 1) * 8);
          if (t >= NTILE - 2) {
            if (lane == 0) mbar_arrive(cx.afree(0));
            if (t == NTILE - 1) {
#pragma unroll
              for (int i = 16; i < 32; i++) S[i] = -INFINITY;
            }
          }
          const bool chg = softmax([&]() {
            if (PXS < 4 && t > 0) {
              const uint32_t db = desc_mn(cx.slot(n - 1));
              wg_fence();
#pragma unroll
              for (int k = PXS; k < 4; k++) wgmma_ss_n256_tb1(acc, dp + k * 2, db + k * 128, 1);
              wg_commit();
            }
          });
          FSTAMP(36 + (t >> 1) * 8);
          wg_wait<0>();
          fence_regs(acc);
          FSTAMP(37 + (t >> 1) * 8);
          if (t > 0) cx.release(n - 1);
          if (__builtin_expect(chg && t > 0, 0)) rescale();
          po(n);
          FSTAMP(38 + (t >> 1) * 8);
          send();
          FSTAMP(39 + (t >> 1) * 8);
        }
        wg_wait<0>();
        fence_regs(acc);
        cx.release(N_ATT0 + 2 * (NTILE - 1 - w));
        if (w == 1) {
          const uint32_t n = N_ATT0 + 2 * (NTILE - 1) + 1;
          recv_px(n, true, 4);
          wg_commit();
          wg_wait<0>();
          fence_regs(acc);
          cx.release(n);
          if (lane == 0) mbar_arrive(cx.afree(1));
        }
        STAMP(9);
        l0 += __shfl_xor_sync(~0u, l0, 1); l1 += __shfl_xor_sync(~0u, l1, 1);
        l0 += __shfl_xor_sync(~0u, l0, 2); l1 += __shfl_xor_sync(~0u, l1, 2);
        uint32_t gp[64];
        {
          const float r0 = __frcp_rn(l0), r1 = __frcp_rn(l1);
#pragma unroll
          for (int j = 0; j < 32; j++) { gp[2 * j] = pack2(acc[4 * j] * r0, acc[4 * j + 1] * r0); gp[2 * j + 1] = pack2(acc[4 * j + 2] * r1, acc[4 * j + 3] * r1); }
        }
        const uint32_t nf = N_FIN0 + w;
        const int La = 64 * (int)rank + rlo, Lb = La + 8;
        const bool va = La >= 1 && La <= 125, vb = Lb <= 125;
        const size_t goff = ((size_t)batch * TT + row0 + rlo) * DD + 256 * w + 8 * c;
        STAMP(10);
        zero_regs(acc);
#pragma unroll 1
        for (int pass = 0; pass < 2; pass++) {
          const int nk = pass ? 4 : 8;
#pragma unroll 1
          for (int kb = 0; kb < nk; kb++) {
            const uint32_t n = nf + 24 * pass + 2 * kb;
            if (pass == 0 && (kb == 0 || kb == 7)) mbar_wait(cx.afull(kb & 1), 0);
            cx.wait_full(n);
            const uint32_t da = desc_k(sb + OFF_Q + (4 * (1 - w) * pass + kb) * CH), db = desc_mn(cx.slot(n));
            wg_fence();
#pragma unroll
            for (int k = 0; k < 4; k++) wgmma_ss_n256_tb1(acc, da + k * 2, db + k * 128, 1);
            wg_commit();
            if (kb > 0) { wg_wait<1>(); cx.release(n - 2); }
          }
          if (pass == 0) {
            STAMP(11);
#pragma unroll
            for (int kb = 0; kb < 4; kb++) {
              const uint32_t n = nf + 16 + 2 * kb;
              cx.wait_full(n);
              const uint32_t db = desc_mn(cx.slot(n));
              wg_fence();
#pragma unroll
              for (int k = 0; k < 4; k++) wgmma_rs_n256_tb1(acc, gp[16 * kb + 4 * k], gp[16 * kb + 4 * k + 1], gp[16 * kb + 4 * k + 2], gp[16 * kb + 4 * k + 3], db + k * 128, 1);
              wg_commit();
              wg_wait<1>();
              cx.release(n - 2);
              if (kb == 0) bar_arrive(7 + w);
              if (kb == 1) {
                bar_sync(8 - w);
#pragma unroll
                for (int ks = 0; ks < 16; ks++)
                  stsm4(sb + OFF_Q + (4 * w + (ks >> 2)) * CH + moff + (((2 * (ks & 3) + mu) ^ mx) << 4), gp[4 * ks], gp[4 * ks + 1], gp[4 * ks + 2], gp[4 * ks + 3]);
                fence_async_smem();
                bar_arrive(9 + w);
              }
            }
            STAMP(12);
            wg_wait<0>();
            fence_regs(gp);
            cx.release(nf + 22);
#pragma unroll
            for (int i = 0; i < 8; i++) {
              const uint4 u = va ? __ldg((const uint4*)(x + goff + 32 * i)) : make_uint4(0, 0, 0, 0);
              const uint4 v = vb ? __ldg((const uint4*)(x + goff + 8 * DD + 32 * i)) : make_uint4(0, 0, 0, 0);
              gp[8 * i] = u.x; gp[8 * i + 1] = u.y; gp[8 * i + 2] = u.z; gp[8 * i + 3] = u.w;
              gp[8 * i + 4] = v.x; gp[8 * i + 5] = v.y; gp[8 * i + 6] = v.z; gp[8 * i + 7] = v.w;
            }
            bar_sync(10 - w);
            STAMP(13);
          }
        }
        wg_wait<0>();
        fence_regs(acc);
        STAMP(14);
#pragma unroll
        for (int i = 0; i < 8; i++) {
          const uint32_t* a = &gp[8 * i];
          const uint32_t* b = &gp[8 * i + 4];
          uint4 oa, ob;
          oa.x = pack2(acc[16 * i] + blo(a[0]), acc[16 * i + 1] + bhi(a[0])); oa.y = pack2(acc[16 * i + 4] + blo(a[1]), acc[16 * i + 5] + bhi(a[1]));
          oa.z = pack2(acc[16 * i + 8] + blo(a[2]), acc[16 * i + 9] + bhi(a[2])); oa.w = pack2(acc[16 * i + 12] + blo(a[3]), acc[16 * i + 13] + bhi(a[3]));
          ob.x = pack2(acc[16 * i + 2] + blo(b[0]), acc[16 * i + 3] + bhi(b[0])); ob.y = pack2(acc[16 * i + 6] + blo(b[1]), acc[16 * i + 7] + bhi(b[1]));
          ob.z = pack2(acc[16 * i + 10] + blo(b[2]), acc[16 * i + 11] + bhi(b[2])); ob.w = pack2(acc[16 * i + 14] + blo(b[3]), acc[16 * i + 15] + bhi(b[3]));
          if (va) *(uint4*)(out + goff + 32 * i) = oa;
          if (vb) *(uint4*)(out + goff + 8 * DD + 32 * i) = ob;
        }
      }
    }
    MARK(mode * 1000 + 999); STAMP(20); GSTAMP(501);
    if (lane == 0) mbar_arrive(cx.dbar());
    if (tid == 0 && mode != 1) atomicAdd(&g_flags[F_DONE * 32], 1u);
    __syncwarp();
    cluster_arrive();
    cluster_wait();
  }
}

typedef CUresult (*EncodeFn)(CUtensorMap*, CUtensorMapDataType, cuuint32_t, void*, const cuuint64_t*, const cuuint64_t*, const cuuint32_t*,
                             const cuuint32_t*, CUtensorMapInterleave, CUtensorMapSwizzle, CUtensorMapL2promotion, CUtensorMapFloatOOBfill);

static void make_map(EncodeFn fn, CUtensorMap* m, void* p, int rows, int cols, int box_rows, int box_blks) {
  cuuint64_t dims[3] = {64, (cuuint64_t)rows, (cuuint64_t)(cols / 64)};
  cuuint64_t strides[2] = {(cuuint64_t)cols * 2, 128};
  cuuint32_t box[3] = {64, (cuuint32_t)box_rows, (cuuint32_t)box_blks};
  cuuint32_t es[3] = {1, 1, 1};
  fn(m, CU_TENSOR_MAP_DATA_TYPE_BFLOAT16, 3, p, dims, strides, box, es, CU_TENSOR_MAP_INTERLEAVE_NONE, CU_TENSOR_MAP_SWIZZLE_128B,
     CU_TENSOR_MAP_L2_PROMOTION_L2_256B, CU_TENSOR_MAP_FLOAT_OOB_FILL_NONE);
}

static void make_map4(EncodeFn fn, CUtensorMap* m, void* p, int rows, int brows, int box_blks) {
  cuuint64_t dims[4] = {64, (cuuint64_t)rows, 8, 2};
  cuuint64_t strides[3] = {DD * 2, 128, (cuuint64_t)brows * DD * 2};
  cuuint32_t box[4] = {64, 64, (cuuint32_t)box_blks, 1};
  cuuint32_t es[4] = {1, 1, 1, 1};
  fn(m, CU_TENSOR_MAP_DATA_TYPE_BFLOAT16, 4, p, dims, strides, box, es, CU_TENSOR_MAP_INTERLEAVE_NONE, CU_TENSOR_MAP_SWIZZLE_128B,
     CU_TENSOR_MAP_L2_PROMOTION_L2_256B, CU_TENSOR_MAP_FLOAT_OOB_FILL_NONE);
}

}

extern "C" void kernel_launch(void* const* d_in, const int* in_sizes, int n_in, void* d_out, int out_size) {
  using namespace bf;
  static EncodeFn fn = nullptr;
  static int fused = 0;
  static void* xa_ptr = nullptr;
  if (!fn) {
    void* p = nullptr;
    cudaDriverEntryPointQueryResult qr;
    cudaGetDriverEntryPoint("cuTensorMapEncodeTiled", &p, cudaEnableDefault, &qr);
    fn = (EncodeFn)p;
    cudaGetSymbolAddress(&xa_ptr, g_xa);
    cudaFuncSetAttribute(bf_kernel, cudaFuncAttributeMaxDynamicSharedMemorySize, SMEM_BYTES);
    cudaLaunchConfig_t cfg = {};
    cfg.gridDim = dim3(NCTA); cfg.blockDim = dim3(384); cfg.dynamicSmemBytes = SMEM_BYTES;
    cudaLaunchAttribute at[1];
    at[0].id = cudaLaunchAttributeClusterDimension; at[0].val.clusterDim.x = 2; at[0].val.clusterDim.y = 1; at[0].val.clusterDim.z = 1;
    cfg.attrs = at; cfg.numAttrs = 1;
    int nc = 0;
    cudaOccupancyMaxActiveClusters(&nc, bf_kernel, &cfg);
    fused = nc >= NCTA / 2;
  }
  Maps maps;
  make_map(fn, &maps.q, d_in[1], 512, 512, 64, 2);
  make_map(fn, &maps.k, d_in[2], 512, 512, 128, 1);
  make_map(fn, &maps.v, d_in[3], 512, 512, 64, 2);
  make_map(fn, &maps.ao, d_in[4], 512, 512, 64, 2);
  make_map(fn, &maps.up, d_in[5], 512, 1024, 64, 4);
  make_map(fn, &maps.dn, d_in[7], 512, 512, 64, 2);
  make_map(fn, &maps.mg, d_in[8], 1024, 512, 64, 2);
  make_map4(fn, &maps.x, d_in[0], TT, TT, 4);
  make_map4(fn, &maps.xs, xa_ptr, TT + 1, TT + 1, 1);
  make_map4(fn, &maps.xl, (uint8_t*)xa_ptr + DD * 2, TT, TT + 1, 2);
  Ptrs wp = {(const uint8_t*)d_in[1], (const uint8_t*)d_in[2], (const uint8_t*)d_in[3], (const uint8_t*)d_in[4],
             (const uint8_t*)d_in[5], (const uint8_t*)d_in[7], (const uint8_t*)d_in[8]};
  const __nv_bfloat16* x = (const __nv_bfloat16*)d_in[0];
  const __nv_bfloat16* dw = (const __nv_bfloat16*)d_in[6];
  __nv_bfloat16* out = (__nv_bfloat16*)d_out;
  if (fused) {
    bf_kernel<<<NCTA, 384, SMEM_BYTES>>>(maps, wp, x, dw, out, 0);
  } else {
    bf_kernel<<<NCTA, 384, SMEM_BYTES>>>(maps, wp, x, dw, out, 1);
    bf_kernel<<<NCTA, 384, SMEM_BYTES>>>(maps, wp, x, dw, out, 2);
  }
}
```

```cpp
#include <cuda_runtime.h>
#include <cuda_bf16.h>
#include <cuda.h>
#include <stdint.h>

namespace bf {

constexpr int TT = 4000, DD = 512, NTILE = 63;
constexpr uint32_t CH = 8192, SLOT = 32768, NS = 5, TILE = 65536;
constexpr uint32_t OFF_Q = NS * SLOT;
constexpr uint32_t OFF_P = OFF_Q + 7 * CH;
constexpr uint32_t OFF_EX = OFF_Q + TILE;
constexpr uint32_t OFF_BAR = OFF_EX + 2048;
constexpr uint32_t SMEM_BYTES = OFF_BAR + 256;
constexpr int NCTA = 132;
#define QKA 3
#define CREG 224
#define PREG 56
#define TSPLIT 4
#define XPACE 400
#define STG(p, v) __stcg(p, v)
#define NOCONV 0
#define MCM 0x00
#define MCF 0
#define PMAX 1024.f
constexpr uint32_t N_ATT0 = 48, N_FIN0 = 48 + 2 * NTILE;

struct Maps { CUtensorMap x, up, q, k, xs, xl, v, ao, dn, mg; };
struct Ptrs { const uint8_t *wq, *wk, *wv, *wao, *wup, *wdn, *wmg; };

__device__ __align__(1024) uint8_t g_xa[2 * (TT + 1) * DD * 2];
__device__ __align__(1024) uint8_t g_uc[256 * TILE];
__device__ __align__(1024) uint8_t g_wqk[8 * TILE];
__device__ __align__(1024) uint8_t g_wf[16 * TILE];
__device__ __align__(1024) float2 g_st[128 * 64 * 2];
__device__ uint32_t g_flags[8 * 32];
constexpr int F_WQK = 0, F_XA = 4, F_WF = 6, F_DONE = 7;

__device__ __forceinline__ uint32_t smem_u32(const void* p) { return (uint32_t)__cvta_generic_to_shared(p); }
__device__ __forceinline__ void mbar_init(uint32_t bar, uint32_t cnt) { asm volatile("mbarrier.init.shared::cta.b64 [%0], %1;" :: "r"(bar), "r"(cnt)); }
__device__ __forceinline__ void mbar_expect_tx(uint32_t bar, uint32_t bytes) { asm volatile("mbarrier.arrive.expect_tx.shared::cta.b64 _, [%0], %1;" :: "r"(bar), "r"(bytes) : "memory"); }
__device__ __forceinline__ void mbar_arrive(uint32_t bar) { asm volatile("mbarrier.arrive.shared::cta.b64 _, [%0];" :: "r"(bar) : "memory"); }
__device__ __forceinline__ void mbar_arrive_cluster(uint32_t a) { asm volatile("mbarrier.arrive.shared::cluster.b64 _, [%0];" :: "r"(a) : "memory"); }
__device__ __forceinline__ void mbar_arrive_cluster_rel(uint32_t a) { asm volatile("mbarrier.arrive.release.cluster.shared::cluster.b64 _, [%0];" :: "r"(a) : "memory"); }
__device__ __forceinline__ void arrive2(uint32_t a, uint32_t b, bool on) {
  asm volatile("{\n.reg .pred p;\nsetp.ne.u32 p, %2, 0;\n@p mbarrier.arrive.shared::cta.b64 _, [%0];\n@p mbarrier.arrive.shared::cluster.b64 _, [%1];\n}\n"
               :: "r"(a), "r"(b), "r"((uint32_t)on) : "memory");
}
__device__ __forceinline__ bool mbar_try_wait(uint32_t bar, uint32_t parity) {
  uint32_t ok;
  asm volatile("{\n.reg .pred p;\nmbarrier.try_wait.parity.shared::cta.b64 p, [%1], %2;\nselp.b32 %0, 1, 0, p;\n}\n" : "=r"(ok) : "r"(bar), "r"(parity) : "memory");
  return ok;
}
__device__ __forceinline__ bool mbar_try_wait_cl(uint32_t bar, uint32_t parity) {
  uint32_t ok;
  asm volatile("{\n.reg .pred p;\nmbarrier.try_wait.parity.acquire.cluster.shared::cta.b64 p, [%1], %2;\nselp.b32 %0, 1, 0, p;\n}\n" : "=r"(ok) : "r"(bar), "r"(parity) : "memory");
  return ok;
}
#define TRAP(a, b) __trap()
#define MARK(c)
#define STAMP(i)
#define PSTAMP(h, i)
#define TSTAMP(i)
#define GSTAMP(i)
#define FSTAMP(i)
__device__ __forceinline__ void mbar_wait(uint32_t bar, uint32_t parity) {
  asm volatile("{\n.reg .pred p;\n.reg .u32 c;\nmov.u32 c, 0;\nWL:\nmbarrier.try_wait.parity.shared::cta.b64 p, [%0], %1;\n@p bra WD;\n"
               "add.u32 c, c, 1;\nsetp.lt.u32 p, c, 0x400000;\n@p bra WL;\ntrap;\nWD:\n}\n" :: "r"(bar), "r"(parity) : "memory");
}
__device__ __forceinline__ void mbar_wait_cl(uint32_t bar, uint32_t parity) {
  asm volatile("{\n.reg .pred p;\n.reg .u32 c;\nmov.u32 c, 0;\nWL:\nmbarrier.try_wait.parity.acquire.cluster.shared::cta.b64 p, [%0], %1;\n@p bra WD;\n"
               "add.u32 c, c, 1;\nsetp.lt.u32 p, c, 0x400000;\n@p bra WL;\ntrap;\nWD:\n}\n" :: "r"(bar), "r"(parity) : "memory");
}
__device__ __forceinline__ uint32_t mapa(uint32_t addr, uint32_t rank) { uint32_t r; asm volatile("mapa.shared::cluster.u32 %0, %1, %2;" : "=r"(r) : "r"(addr), "r"(rank)); return r; }
__device__ __forceinline__ void bulk_g2s(uint32_t dst, const void* src, uint32_t bytes, uint32_t bar) {
  asm volatile("cp.async.bulk.shared::cluster.global.mbarrier::complete_tx::bytes [%0], [%1], %2, [%3];" :: "r"(dst), "l"(src), "r"(bytes), "r"(bar) : "memory");
}
__device__ __forceinline__ void bulk_g2s_mc(uint32_t dst, const void* src, uint32_t bytes, uint32_t bar) {
  asm volatile("cp.async.bulk.shared::cluster.global.mbarrier::complete_tx::bytes.multicast::cluster [%0], [%1], %2, [%3], %4;" :: "r"(dst), "l"(src), "r"(bytes), "r"(bar), "h"((uint16_t)3) : "memory");
}
__device__ __forceinline__ void tma3d(uint32_t dst, const CUtensorMap* m, int c1, int c2, uint32_t bar) {
  asm volatile("cp.async.bulk.tensor.3d.shared::cluster.global.mbarrier::complete_tx::bytes [%0], [%1, {%3, %4, %5}], [%2];"
               :: "r"(dst), "l"(m), "r"(bar), "r"(0), "r"(c1), "r"(c2) : "memory");
}
__device__ __forceinline__ void tma3d_mc(uint32_t dst, const CUtensorMap* m, int c1, int c2, uint32_t bar) {
  asm volatile("cp.async.bulk.tensor.3d.shared::cluster.global.mbarrier::complete_tx::bytes.multicast::cluster [%0], [%1, {%3, %4, %5}], [%2], %6;"
               :: "r"(dst), "l"(m), "r"(bar), "r"(0), "r"(c1), "r"(c2), "h"((uint16_t)3) : "memory");
}
__device__ __forceinline__ void tma4d(uint32_t dst, const CUtensorMap* m, int c1, int c2, int c3, uint32_t bar) {
  asm volatile("cp.async.bulk.tensor.4d.shared::cluster.global.mbarrier::complete_tx::bytes [%0], [%1, {%3, %4, %5, %6}], [%2];"
               :: "r"(dst), "l"(m), "r"(bar), "r"(0), "r"(c1), "r"(c2), "r"(c3) : "memory");
}
__device__ __forceinline__ void tma4d_mc(uint32_t dst, const CUtensorMap* m, int c1, int c2, int c3, uint32_t bar) {
  asm volatile("cp.async.bulk.tensor.4d.shared::cluster.global.mbarrier::complete_tx::bytes.multicast::cluster [%0], [%1, {%3, %4, %5, %6}], [%2], %7;"
               :: "r"(dst), "l"(m), "r"(bar), "r"(0), "r"(c1), "r"(c2), "r"(c3), "h"((uint16_t)3) : "memory");
}
__device__ __forceinline__ void tma4d_store(const CUtensorMap* m, uint32_t src, int c1, int c2, int c3) {
  asm volatile("cp.async.bulk.tensor.4d.global.shared::cta.bulk_group [%0, {%2, %3, %4, %5}], [%1];"
               :: "l"(m), "r"(src), "r"(0), "r"(c1), "r"(c2), "r"(c3) : "memory");
}
__device__ __forceinline__ void l2_prefetch(const void* p, uint32_t bytes) { asm volatile("cp.async.bulk.prefetch.L2.global [%0], %1;" :: "l"(p), "r"(bytes) : "memory"); }
__device__ __forceinline__ void map_prefetch(const CUtensorMap* m) { asm volatile("prefetch.tensormap [%0];" :: "l"(m) : "memory"); }
__device__ __forceinline__ bool elect_one() {
  uint32_t p;
  asm volatile("{\n.reg .pred P;\nelect.sync _|P, 0xffffffff;\nselp.b32 %0, 1, 0, P;\n}\n" : "=r"(p));
  return p;
}
__device__ __forceinline__ void wg_fence() { asm volatile("wgmma.fence.sync.aligned;" ::: "memory"); }
__device__ __forceinline__ void wg_commit() { asm volatile("wgmma.commit_group.sync.aligned;" ::: "memory"); }
template <int N> __device__ __forceinline__ void wg_wait() { asm volatile("wgmma.wait_group.sync.aligned %0;" :: "n"(N) : "memory"); }
__device__ __forceinline__ void cluster_arrive() { asm volatile("barrier.cluster.arrive.relaxed.aligned;" ::: "memory"); }
__device__ __forceinline__ void cluster_wait() { asm volatile("barrier.cluster.wait.aligned;" ::: "memory"); }
__device__ __forceinline__ uint32_t cluster_rank() { uint32_t r; asm volatile("mov.u32 %0, %%cluster_ctarank;" : "=r"(r)); return r; }
__device__ __forceinline__ void bar_sync(int id) { asm volatile("bar.sync %0, 256;" :: "r"(id) : "memory"); }
__device__ __forceinline__ void bar_sync_n(int id, int n) { asm volatile("bar.sync %0, %1;" :: "r"(id), "r"(n) : "memory"); }
__device__ __forceinline__ void bar_arrive(int id) { asm volatile("bar.arrive %0, 256;" :: "r"(id) : "memory"); }
__device__ __forceinline__ void fence_async_smem() { asm volatile("fence.proxy.async.shared::cta;" ::: "memory"); }
__device__ __forceinline__ void fence_async_all() { asm volatile("fence.proxy.async;" ::: "memory"); }
__device__ __forceinline__ uint32_t desc_k(uint32_t addr) { return ((addr & 0x3FFFF) >> 4) | (1u << 16); }
__device__ __forceinline__ uint32_t desc_mn(uint32_t addr) { return ((addr & 0x3FFFF) >> 4) | ((CH >> 4) << 16); }
template <int R> __device__ __forceinline__ void reg_alloc() { asm volatile("setmaxnreg.inc.sync.aligned.u32 %0;" :: "n"(R)); }
template <int R> __device__ __forceinline__ void reg_dealloc() { asm volatile("setmaxnreg.dec.sync.aligned.u32 %0;" :: "n"(R)); }
template <int V> struct IC { static constexpr int value = V; };
template <int N> __device__ __forceinline__ void fence_regs(float (&r)[N]) {
#pragma unroll
  for (int i = 0; i < N; i++) asm volatile("" : "+f"(r[i]) :: "memory");
}
template <int N> __device__ __forceinline__ void fence_regs(uint32_t (&r)[N]) {
#pragma unroll
  for (int i = 0; i < N; i++) asm volatile("" : "+r"(r[i]) :: "memory");
}
template <int N> __device__ __forceinline__ void zero_regs(float (&r)[N]) {
#pragma unroll
  for (int i = 0; i < N; i++) r[i] = 0.f;
  fence_regs(r);
}
__device__ __forceinline__ uint32_t pack2(float lo, float hi) { uint32_t r; asm("cvt.rn.bf16x2.f32 %0, %1, %2;" : "=r"(r) : "f"(hi), "f"(lo)); return r; }
__device__ __forceinline__ float blo(uint32_t v) { return __uint_as_float(v << 16); }
__device__ __forceinline__ float bhi(uint32_t v) { return __uint_as_float(v & 0xFFFF0000u); }
__device__ __forceinline__ float ex2(float x) { float r; asm("ex2.approx.ftz.f32 %0, %1;" : "=f"(r) : "f"(x)); return r; }
__device__ __forceinline__ float gelu2(float h) {
  float z = h * fmaf(h * h, 8.f * 0.044715f * 0.7978845608028654f, 2.f * 0.7978845608028654f), t;
  asm("tanh.approx.f32 %0, %1;" : "=f"(t) : "f"(z));
  return fmaf(h, t, h);
}
__device__ __forceinline__ uint32_t hfma2(uint32_t a, uint32_t b, uint32_t c) { uint32_t r; asm("fma.rn.bf16x2 %0, %1, %2, %3;" : "=r"(r) : "r"(a), "r"(b), "r"(c)); return r; }
__device__ __forceinline__ uint32_t hmul2(uint32_t a, uint32_t b) { uint32_t r; asm("mul.rn.bf16x2 %0, %1, %2;" : "=r"(r) : "r"(a), "r"(b)); return r; }
__device__ __forceinline__ void stsm4(uint32_t addr, uint32_t a, uint32_t b, uint32_t c, uint32_t d) {
  asm volatile("stmatrix.sync.aligned.m8n8.x4.shared.b16 [%0], {%1, %2, %3, %4};" :: "r"(addr), "r"(a), "r"(b), "r"(c), "r"(d) : "memory");
}
__device__ __forceinline__ void ldsm4(uint32_t addr, uint32_t& a, uint32_t& b, uint32_t& c, uint32_t& d) {
  asm volatile("ldmatrix.sync.aligned.m8n8.x4.shared.b16 {%0, %1, %2, %3}, [%4];" : "=r"(a), "=r"(b), "=r"(c), "=r"(d) : "r"(addr) : "memory");
}
__device__ __forceinline__ void sts128(uint32_t addr, uint32_t a, uint32_t b, uint32_t c, uint32_t d) {
  asm volatile("st.shared.v4.b32 [%0], {%1, %2, %3, %4};" :: "r"(addr), "r"(a), "r"(b), "r"(c), "r"(d) : "memory");
}
__device__ __forceinline__ void lds128(uint32_t addr, uint32_t (&v)[4]) {
  asm volatile("ld.shared.v4.b32 {%0, %1, %2, %3}, [%4];" : "=r"(v[0]), "=r"(v[1]), "=r"(v[2]), "=r"(v[3]) : "r"(addr) : "memory");
}
__device__ __forceinline__ uint32_t ld_relaxed(const uint32_t* p) { uint32_t v; asm volatile("ld.relaxed.gpu.global.u32 %0, [%1];" : "=r"(v) : "l"(p) : "memory"); return v; }
__device__ __forceinline__ int fresh_tid() { int t; asm volatile("mov.u32 %0, %%tid.x;" : "=r"(t)); return t; }
__device__ __forceinline__ void fence_gpu() { asm volatile("fence.acq_rel.gpu;" ::: "memory"); }
__device__ __forceinline__ void wait_flag(int idx, uint32_t target) {
  uint32_t i = 0;
#pragma unroll 1
  while ((int)(ld_relaxed(&g_flags[idx * 32]) - target) < 0) { __nanosleep(idx == F_WF ? 1000 : 32); if (++i > (1u << 22)) TRAP(idx, target); }
  fence_async_all();
}
__device__ __forceinline__ void signal_flag(int idx) {
  fence_async_all();
  fence_gpu();
  asm volatile("red.relaxed.gpu.global.add.u32 [%0], 1;" :: "l"(&g_flags[idx * 32]) : "memory");
}

__device__ __forceinline__ void wgmma_ss_n256_tb1(float (&d)[128], uint32_t da, uint32_t db, int scale_d) {
  asm volatile("{\n.reg .pred p;\n.reg .b64 da, db;\nsetp.ne.b32 p, %130, 0;\nmov.b64 da, {%128, 0x40000040};\nmov.b64 db, {%129, 0x40000040};\n"
    "wgmma.mma_async.sync.aligned.m64n256k16.f32.bf16.bf16 {%0, %1, %2, %3, %4, %5, %6, %7, %8, %9, %10, %11, %12, %13, %14, %15, %16, %17, %18, %19, %20, %21, %22, %23, %24, %25, %26, %27, %28, %29, %30, %31, %32, %33, %34, %35, %36, %37, %38, %39, %40, %41, %42, %43, %44, %45, %46, %47, %48, %49, %50, %51, %52, %53, %54, %55, %56, %57, %58, %59, %60, %61, %62, %63, %64, %65, %66, %67, %68, %69, %70, %71, %72, %73, %74, %75, %76, %77, %78, %79, %80, %81, %82, %83, %84, %85, %86, %87, %88, %89, %90, %91, %92, %93, %94, %95, %96, %97, %98, %99, %100, %101, %102, %103, %104, %105, %106, %107, %108, %109, %110, %111, %112, %113, %114, %115, %116, %117, %118, %119, %120, %121, %122, %123, %124, %125, %126, %127}, da, db, p, 1, 1, 0, 1;\n}\n"
    : "+f"(d[0]), "+f"(d[1]), "+f"(d[2]), "+f"(d[3]), "+f"(d[4]), "+f"(d[5]), "+f"(d[6]), "+f"(d[7]), "+f"(d[8]), "+f"(d[9]), "+f"(d[10]), "+f"(d[11]), "+f"(d[12]), "+f"(d[13]), "+f"(d[14]), "+f"(d[15]), "+f"(d[16]), "+f"(d[17]), "+f"(d[18]), "+f"(d[19]), "+f"(d[20]), "+f"(d[21]), "+f"(d[22]), "+f"(d[23]), "+f"(d[24]), "+f"(d[25]), "+f"(d[26]), "+f"(d[27]), "+f"(d[28]), "+f"(d[29]), "+f"(d[30]), "+f"(d[31]), "+f"(d[32]), "+f"(d[33]), "+f"(d[34]), "+f"(d[35]), "+f"(d[36]), "+f"(d[37]), "+f"(d[38]), "+f"(d[39]), "+f"(d[40]), "+f"(d[41]), "+f"(d[42]), "+f"(d[43]), "+f"(d[44]), "+f"(d[45]), "+f"(d[46]), "+f"(d[47]), "+f"(d[48]), "+f"(d[49]), "+f"(d[50]), "+f"(d[51]), "+f"(d[52]), "+f"(d[53]), "+f"(d[54]), "+f"(d[55]), "+f"(d[56]), "+f"(d[57]), "+f"(d[58]), "+f"(d[59]), "+f"(d[60]), "+f"(d[61]), "+f"(d[62]), "+f"(d[63]), "+f"(d[64]), "+f"(d[65]), "+f"(d[66]), "+f"(d[67]), "+f"(d[68]), "+f"(d[69]), "+f"(d[70]), "+f"(d[71]), "+f"(d[72]), "+f"(d[73]), "+f"(d[74]), "+f"(d[75]), "+f"(d[76]), "+f"(d[77]), "+f"(d[78]), "+f"(d[79]), "+f"(d[80]), "+f"(d[81]), "+f"(d[82]), "+f"(d[83]), "+f"(d[84]), "+f"(d[85]), "+f"(d[86]), "+f"(d[87]), "+f"(d[88]), "+f"(d[89]), "+f"(d[90]), "+f"(d[91]), "+f"(d[92]), "+f"(d[93]), "+f"(d[94]), "+f"(d[95]), "+f"(d[96]), "+f"(d[97]), "+f"(d[98]), "+f"(d[99]), "+f"(d[100]), "+f"(d[101]), "+f"(d[102]), "+f"(d[103]), "+f"(d[104]), "+f"(d[105]), "+f"(d[106]), "+f"(d[107]), "+f"(d[108]), "+f"(d[109]), "+f"(d[110]), "+f"(d[111]), "+f"(d[112]), "+f"(d[113]), "+f"(d[114]), "+f"(d[115]), "+f"(d[116]), "+f"(d[117]), "+f"(d[118]), "+f"(d[119]), "+f"(d[120]), "+f"(d[121]), "+f"(d[122]), "+f"(d[123]), "+f"(d[124]), "+f"(d[125]), "+f"(d[126]), "+f"(d[127])
    : "r"(da), "r"(db), "r"(scale_d));
}

__device__ __forceinline__ void wgmma_ss_n256_tb0(float (&d)[128], uint32_t da, uint32_t db, int scale_d) {
  asm volatile("{\n.reg .pred p;\n.reg .b64 da, db;\nsetp.ne.b32 p, %130, 0;\nmov.b64 da, {%128, 0x40000040};\nmov.b64 db, {%129, 0x40000040};\n"
    "wgmma.mma_async.sync.aligned.m64n256k16.f32.bf16.bf16 {%0, %1, %2, %3, %4, %5, %6, %7, %8, %9, %10, %11, %12, %13, %14, %15, %16, %17, %18, %19, %20, %21, %22, %23, %24, %25, %26, %27, %28, %29, %30, %31, %32, %33, %34, %35, %36, %37, %38, %39, %40, %41, %42, %43, %44, %45, %46, %47, %48, %49, %50, %51, %52, %53, %54, %55, %56, %57, %58, %59, %60, %61, %62, %63, %64, %65, %66, %67, %68, %69, %70, %71, %72, %73, %74, %75, %76, %77, %78, %79, %80, %81, %82, %83, %84, %85, %86, %87, %88, %89, %90, %91, %92, %93, %94, %95, %96, %97, %98, %99, %100, %101, %102, %103, %104, %105, %106, %107, %108, %109, %110, %111, %112, %113, %114, %115, %116, %117, %118, %119, %120, %121, %122, %123, %124, %125, %126, %127}, da, db, p, 1, 1, 0, 0;\n}\n"
    : "+f"(d[0]), "+f"(d[1]), "+f"(d[2]), "+f"(d[3]), "+f"(d[4]), "+f"(d[5]), "+f"(d[6]), "+f"(d[7]), "+f"(d[8]), "+f"(d[9]), "+f"(d[10]), "+f"(d[11]), "+f"(d[12]), "+f"(d[13]), "+f"(d[14]), "+f"(d[15]), "+f"(d[16]), "+f"(d[17]), "+f"(d[18]), "+f"(d[19]), "+f"(d[20]), "+f"(d[21]), "+f"(d[22]), "+f"(d[23]), "+f"(d[24]), "+f"(d[25]), "+f"(d[26]), "+f"(d[27]), "+f"(d[28]), "+f"(d[29]), "+f"(d[30]), "+f"(d[31]), "+f"(d[32]), "+f"(d[33]), "+f"(d[34]), "+f"(d[35]), "+f"(d[36]), "+f"(d[37]), "+f"(d[38]), "+f"(d[39]), "+f"(d[40]), "+f"(d[41]), "+f"(d[42]), "+f"(d[43]), "+f"(d[44]), "+f"(d[45]), "+f"(d[46]), "+f"(d[47]), "+f"(d[48]), "+f"(d[49]), "+f"(d[50]), "+f"(d[51]), "+f"(d[52]), "+f"(d[53]), "+f"(d[54]), "+f"(d[55]), "+f"(d[56]), "+f"(d[57]), "+f"(d[58]), "+f"(d[59]), "+f"(d[60]), "+f"(d[61]), "+f"(d[62]), "+f"(d[63]), "+f"(d[64]), "+f"(d[65]), "+f"(d[66]), "+f"(d[67]), "+f"(d[68]), "+f"(d[69]), "+f"(d[70]), "+f"(d[71]), "+f"(d[72]), "+f"(d[73]), "+f"(d[74]), "+f"(d[75]), "+f"(d[76]), "+f"(d[77]), "+f"(d[78]), "+f"(d[79]), "+f"(d[80]), "+f"(d[81]), "+f"(d[82]), "+f"(d[83]), "+f"(d[84]), "+f"(d[85]), "+f"(d[86]), "+f"(d[87]), "+f"(d[88]), "+f"(d[89]), "+f"(d[90]), "+f"(d[91]), "+f"(d[92]), "+f"(d[93]), "+f"(d[94]), "+f"(d[95]), "+f"(d[96]), "+f"(d[97]), "+f"(d[98]), "+f"(d[99]), "+f"(d[100]), "+f"(d[101]), "+f"(d[102]), "+f"(d[103]), "+f"(d[104]), "+f"(d[105]), "+f"(d[106]), "+f"(d[107]), "+f"(d[108]), "+f"(d[109]), "+f"(d[110]), "+f"(d[111]), "+f"(d[112]), "+f"(d[113]), "+f"(d[114]), "+f"(d[115]), "+f"(d[116]), "+f"(d[117]), "+f"(d[118]), "+f"(d[119]), "+f"(d[120]), "+f"(d[121]), "+f"(d[122]), "+f"(d[123]), "+f"(d[124]), "+f"(d[125]), "+f"(d[126]), "+f"(d[127])
    : "r"(da), "r"(db), "r"(scale_d));
}

__device__ __forceinline__ void wgmma_rs_n256_tb1(float (&d)[128], uint32_t a0, uint32_t a1, uint32_t a2, uint32_t a3, uint32_t db, int scale_d) {
  asm volatile("{\n.reg .pred p;\n.reg .b64 db;\nsetp.ne.b32 p, %133, 0;\nmov.b64 db, {%132, 0x40000040};\n"
    "wgmma.mma_async.sync.aligned.m64n256k16.f32.bf16.bf16 {%0, %1, %2, %3, %4, %5, %6, %7, %8, %9, %10, %11, %12, %13, %14, %15, %16, %17, %18, %19, %20, %21, %22, %23, %24, %25, %26, %27, %28, %29, %30, %31, %32, %33, %34, %35, %36, %37, %38, %39, %40, %41, %42, %43, %44, %45, %46, %47, %48, %49, %50, %51, %52, %53, %54, %55, %56, %57, %58, %59, %60, %61, %62, %63, %64, %65, %66, %67, %68, %69, %70, %71, %72, %73, %74, %75, %76, %77, %78, %79, %80, %81, %82, %83, %84, %85, %86, %87, %88, %89, %90, %91, %92, %93, %94, %95, %96, %97, %98, %99, %100, %101, %102, %103, %104, %105, %106, %107, %108, %109, %110, %111, %112, %113, %114, %115, %116, %117, %118, %119, %120, %121, %122, %123, %124, %125, %126, %127}, {%128, %129, %130, %131}, db, p, 1, 1, 1;\n}\n"
    : "+f"(d[0]), "+f"(d[1]), "+f"(d[2]), "+f"(d[3]), "+f"(d[4]), "+f"(d[5]), "+f"(d[6]), "+f"(d[7]), "+f"(d[8]), "+f"(d[9]), "+f"(d[10]), "+f"(d[11]), "+f"(d[12]), "+f"(d[13]), "+f"(d[14]), "+f"(d[15]), "+f"(d[16]), "+f"(d[17]), "+f"(d[18]), "+f"(d[19]), "+f"(d[20]), "+f"(d[21]), "+f"(d[22]), "+f"(d[23]), "+f"(d[24]), "+f"(d[25]), "+f"(d[26]), "+f"(d[27]), "+f"(d[28]), "+f"(d[29]), "+f"(d[30]), "+f"(d[31]), "+f"(d[32]), "+f"(d[33]), "+f"(d[34]), "+f"(d[35]), "+f"(d[36]), "+f"(d[37]), "+f"(d[38]), "+f"(d[39]), "+f"(d[40]), "+f"(d[41]), "+f"(d[42]), "+f"(d[43]), "+f"(d[44]), "+f"(d[45]), "+f"(d[46]), "+f"(d[47]), "+f"(d[48]), "+f"(d[49]), "+f"(d[50]), "+f"(d[51]), "+f"(d[52]), "+f"(d[53]), "+f"(d[54]), "+f"(d[55]), "+f"(d[56]), "+f"(d[57]), "+f"(d[58]), "+f"(d[59]), "+f"(d[60]), "+f"(d[61]), "+f"(d[62]), "+f"(d[63]), "+f"(d[64]), "+f"(d[65]), "+f"(d[66]), "+f"(d[67]), "+f"(d[68]), "+f"(d[69]), "+f"(d[70]), "+f"(d[71]), "+f"(d[72]), "+f"(d[73]), "+f"(d[74]), "+f"(d[75]), "+f"(d[76]), "+f"(d[77]), "+f"(d[78]), "+f"(d[79]), "+f"(d[80]), "+f"(d[81]), "+f"(d[82]), "+f"(d[83]), "+f"(d[84]), "+f"(d[85]), "+f"(d[86]), "+f"(d[87]), "+f"(d[88]), "+f"(d[89]), "+f"(d[90]), "+f"(d[91]), "+f"(d[92]), "+f"(d[93]), "+f"(d[94]), "+f"(d[95]), "+f"(d[96]), "+f"(d[97]), "+f"(d[98]), "+f"(d[99]), "+f"(d[100]), "+f"(d[101]), "+f"(d[102]), "+f"(d[103]), "+f"(d[104]), "+f"(d[105]), "+f"(d[106]), "+f"(d[107]), "+f"(d[108]), "+f"(d[109]), "+f"(d[110]), "+f"(d[111]), "+f"(d[112]), "+f"(d[113]), "+f"(d[114]), "+f"(d[115]), "+f"(d[116]), "+f"(d[117]), "+f"(d[118]), "+f"(d[119]), "+f"(d[120]), "+f"(d[121]), "+f"(d[122]), "+f"(d[123]), "+f"(d[124]), "+f"(d[125]), "+f"(d[126]), "+f"(d[127])
    : "r"(a0), "r"(a1), "r"(a2), "r"(a3), "r"(db), "r"(scale_d));
}

__device__ __forceinline__ void wgmma_ss_n64_tb0(float (&d)[32], uint32_t da, uint32_t db, int scale_d) {
  asm volatile("{\n.reg .pred p;\n.reg .b64 da, db;\nsetp.ne.b32 p, %34, 0;\nmov.b64 da, {%32, 0x40000040};\nmov.b64 db, {%33, 0x40000040};\n"
    "wgmma.mma_async.sync.aligned.m64n64k16.f32.bf16.bf16 {%0, %1, %2, %3, %4, %5, %6, %7, %8, %9, %10, %11, %12, %13, %14, %15, %16, %17, %18, %19, %20, %21, %22, %23, %24, %25, %26, %27, %28, %29, %30, %31}, da, db, p, 1, 1, 0, 0;\n}\n"
    : "+f"(d[0]), "+f"(d[1]), "+f"(d[2]), "+f"(d[3]), "+f"(d[4]), "+f"(d[5]), "+f"(d[6]), "+f"(d[7]), "+f"(d[8]), "+f"(d[9]), "+f"(d[10]), "+f"(d[11]), "+f"(d[12]), "+f"(d[13]), "+f"(d[14]), "+f"(d[15]), "+f"(d[16]), "+f"(d[17]), "+f"(d[18]), "+f"(d[19]), "+f"(d[20]), "+f"(d[21]), "+f"(d[22]), "+f"(d[23]), "+f"(d[24]), "+f"(d[25]), "+f"(d[26]), "+f"(d[27]), "+f"(d[28]), "+f"(d[29]), "+f"(d[30]), "+f"(d[31])
    : "r"(da), "r"(db), "r"(scale_d));
}

__device__ __forceinline__ void wgmma_rs_n64_tb0(float (&d)[32], uint32_t a0, uint32_t a1, uint32_t a2, uint32_t a3, uint32_t db, int scale_d) {
  asm volatile("{\n.reg .pred p;\n.reg .b64 db;\nsetp.ne.b32 p, %37, 0;\nmov.b64 db, {%36, 0x40000040};\n"
    "wgmma.mma_async.sync.aligned.m64n64k16.f32.bf16.bf16 {%0, %1, %2, %3, %4, %5, %6, %7, %8, %9, %10, %11, %12, %13, %14, %15, %16, %17, %18, %19, %20, %21, %22, %23, %24, %25, %26, %27, %28, %29, %30, %31}, {%32, %33, %34, %35}, db, p, 1, 1, 0;\n}\n"
    : "+f"(d[0]), "+f"(d[1]), "+f"(d[2]), "+f"(d[3]), "+f"(d[4]), "+f"(d[5]), "+f"(d[6]), "+f"(d[7]), "+f"(d[8]), "+f"(d[9]), "+f"(d[10]), "+f"(d[11]), "+f"(d[12]), "+f"(d[13]), "+f"(d[14]), "+f"(d[15]), "+f"(d[16]), "+f"(d[17]), "+f"(d[18]), "+f"(d[19]), "+f"(d[20]), "+f"(d[21]), "+f"(d[22]), "+f"(d[23]), "+f"(d[24]), "+f"(d[25]), "+f"(d[26]), "+f"(d[27]), "+f"(d[28]), "+f"(d[29]), "+f"(d[30]), "+f"(d[31])
    : "r"(a0), "r"(a1), "r"(a2), "r"(a3), "r"(db), "r"(scale_d));
}

template <int O>
__device__ __forceinline__ void wgmma_ss_n128_tb1(float (&d)[128], uint32_t da, uint32_t db, int scale_d) {
  asm volatile("{\n.reg .pred p;\n.reg .b64 da, db;\nsetp.ne.b32 p, %66, 0;\nmov.b64 da, {%64, 0x40000040};\nmov.b64 db, {%65, 0x40000040};\n"
    "wgmma.mma_async.sync.aligned.m64n128k16.f32.bf16.bf16 {%0, %1, %2, %3, %4, %5, %6, %7, %8, %9, %10, %11, %12, %13, %14, %15, %16, %17, %18, %19, %20, %21, %22, %23, %24, %25, %26, %27, %28, %29, %30, %31, %32, %33, %34, %35, %36, %37, %38, %39, %40, %41, %42, %43, %44, %45, %46, %47, %48, %49, %50, %51, %52, %53, %54, %55, %56, %57, %58, %59, %60, %61, %62, %63}, da, db, p, 1, 1, 0, 1;\n}\n"
    : "+f"(d[O + 0]), "+f"(d[O + 1]), "+f"(d[O + 2]), "+f"(d[O + 3]), "+f"(d[O + 4]), "+f"(d[O + 5]), "+f"(d[O + 6]), "+f"(d[O + 7]), "+f"(d[O + 8]), "+f"(d[O + 9]), "+f"(d[O + 10]), "+f"(d[O + 11]), "+f"(d[O + 12]), "+f"(d[O + 13]), "+f"(d[O + 14]), "+f"(d[O + 15]), "+f"(d[O + 16]), "+f"(d[O + 17]), "+f"(d[O + 18]), "+f"(d[O + 19]), "+f"(d[O + 20]), "+f"(d[O + 21]), "+f"(d[O + 22]), "+f"(d[O + 23]), "+f"(d[O + 24]), "+f"(d[O + 25]), "+f"(d[O + 26]), "+f"(d[O + 27]), "+f"(d[O + 28]), "+f"(d[O + 29]), "+f"(d[O + 30]), "+f"(d[O + 31]), "+f"(d[O + 32]), "+f"(d[O + 33]), "+f"(d[O + 34]), "+f"(d[O + 35]), "+f"(d[O + 36]), "+f"(d[O + 37]), "+f"(d[O + 38]), "+f"(d[O + 39]), "+f"(d[O + 40]), "+f"(d[O + 41]), "+f"(d[O + 42]), "+f"(d[O + 43]), "+f"(d[O + 44]), "+f"(d[O + 45]), "+f"(d[O + 46]), "+f"(d[O + 47]), "+f"(d[O + 48]), "+f"(d[O + 49]), "+f"(d[O + 50]), "+f"(d[O + 51]), "+f"(d[O + 52]), "+f"(d[O + 53]), "+f"(d[O + 54]), "+f"(d[O + 55]), "+f"(d[O + 56]), "+f"(d[O + 57]), "+f"(d[O + 58]), "+f"(d[O + 59]), "+f"(d[O + 60]), "+f"(d[O + 61]), "+f"(d[O + 62]), "+f"(d[O + 63])
    : "r"(da), "r"(db), "r"(scale_d));
}

struct Ctx {
  uint32_t sb;
  uint32_t pdelta;
  uint32_t fb, ph;
  bool l0;
  __device__ __forceinline__ uint32_t slot(uint32_t n) const { return sb + (n % NS) * SLOT; }
  __device__ __forceinline__ uint32_t full(uint32_t n, uint32_t w) const { return sb + OFF_BAR + 40 * w + 8 * (n % NS); }
  __device__ __forceinline__ uint32_t empty(uint32_t n) const { return sb + OFF_BAR + 80 + 8 * (n % NS); }
  __device__ __forceinline__ uint32_t afull(int h) const { return sb + OFF_BAR + 120 + 8 * h; }
  __device__ __forceinline__ uint32_t afree(int h) const { return sb + OFF_BAR + 136 + 8 * h; }
  __device__ __forceinline__ uint32_t gbar() const { return sb + OFF_BAR + 152; }
  __device__ __forceinline__ uint32_t dbar() const { return sb + OFF_BAR + 160; }
  __device__ __forceinline__ uint32_t xbar() const { return sb + OFF_BAR + 168; }
  __device__ __forceinline__ uint32_t sbar(int w) const { return sb + OFF_BAR + 176 + 8 * w; }
  __device__ __forceinline__ void wait_full(uint32_t n) {
    const uint32_t s = n % NS;
    mbar_wait(fb + 8 * s, (ph >> s) & 1);
    ph ^= 1u << s;
  }
  __device__ __forceinline__ uint32_t cbar() const { return sb + OFF_BAR + 192; }
  __device__ __forceinline__ uint32_t fbar(int i) const { return sb + OFF_BAR + 200 + 8 * i; }
  template <int LO> __device__ __forceinline__ uint32_t rdelta(uint32_t n) const { return n - LO < N_FIN0 - N_ATT0 || (n < N_ATT0 ? (MCM >> ((n + NS) & 7) & 1) : MCF) ? pdelta : 0; }
  template <int LO = N_ATT0 - NS> __device__ __forceinline__ void release(uint32_t n) const { const uint32_t e = empty(n); arrive2(e, e + rdelta<LO>(n), l0); }
};

template <int TB, int LO, class Pre, class Post>
__device__ __forceinline__ void gemm8(Ctx& cx, float (&acc)[128], uint32_t n0, Pre pre, Post post) {
  zero_regs(acc);
  uint32_t s = n0 % NS, e = 0, e2 = 0;
  uint32_t fb = cx.fb + 8 * s, par = (cx.ph >> s) & 1;
  uint32_t da = desc_k(cx.sb + OFF_Q), db = TB ? desc_mn(cx.sb + s * SLOT) : desc_k(cx.sb + s * SLOT);
#pragma unroll 1
  for (int kb = 0; kb < 8; kb++) {
    pre(kb);
    if (n0 < 48) STAMP(240 + n0 + kb);
    mbar_wait(fb, par);
    wg_fence();
#pragma unroll
    for (int k = 0; k < 4; k++) {
      if (TB) wgmma_ss_n256_tb1(acc, da + k * 2, db + k * 128, 1);
      else wgmma_ss_n256_tb0(acc, da + k * 2, db + k * 2, 1);
    }
    wg_commit();
    const uint32_t pe = e, pe2 = e2;
    e = cx.sb + OFF_BAR + 80 + 8 * s;
    e2 = e + cx.rdelta<LO>(n0 + kb);
    cx.ph ^= 1u << s;
    db += s == NS - 1 ? -(NS - 1) * (SLOT >> 4) : (SLOT >> 4);
    s = s == NS - 1 ? 0 : s + 1;
    fb = cx.fb + 8 * s; par = (cx.ph >> s) & 1;
    da += CH >> 4;
    wg_wait<1>();
    arrive2(pe, pe2, kb > 0 && cx.l0);
    if (kb > 0) post(kb - 1);
  }
  wg_wait<0>();
  fence_regs(acc);
  arrive2(e, e2, cx.l0);
  post(7);
}

__device__ __forceinline__ int sigma(int r) { return (r & ~30) | ((r & 6) << 2) | ((r & 24) >> 2); }

__global__ void __cluster_dims__(2, 1, 1) __launch_bounds__(384, 1)
bf_kernel(const __grid_constant__ Maps maps, const __grid_constant__ Ptrs wp, const __nv_bfloat16* __restrict__ x,
          const __nv_bfloat16* __restrict__ dw, __nv_bfloat16* __restrict__ out, int mode) {
  extern __shared__ __align__(1024) uint8_t smem_raw[];
  if (threadIdx.x < 256) { GSTAMP(502); STAMP(503); }
  Ctx cx;
  cx.sb = smem_u32(smem_raw);
  const uint32_t sb = cx.sb;
  const int tid = threadIdx.x, lane = tid & 31, warp = __shfl_sync(~0u, tid >> 5, 0);
  const uint32_t rank = cluster_rank();
  cx.pdelta = mapa(sb, rank ^ 1) - sb;
  const int cid = blockIdx.x >> 1;
  const bool spare = cid < 2;
  const int pairi = cid - 2, batch = pairi >> 5, pp = pairi & 31;
  const int row0 = 125 * pp - 1 + 64 * (int)rank;
  if (tid == 0) {
    mbar_init(cx.xbar(), 1);
    asm volatile("fence.mbarrier_init.release.cluster;" ::: "memory");
    if (!spare) {
      mbar_expect_tx(cx.xbar(), TILE);
      tma4d(sb + OFF_Q, &maps.x, row0, 0, batch, cx.xbar());
      tma4d(sb + OFF_Q + SLOT, &maps.x, row0, 4, batch, cx.xbar());
    }
    if (sb & 1023) TRAP(sb, 12345);
    TSTAMP(490);
  } else if (tid == 32) {
#pragma unroll 1
    for (int i = 0; i < (int)NS; i++) { mbar_init(cx.full(i, 0), 1); mbar_init(cx.full(i, 1), 1); mbar_init(cx.empty(i), 8); }
    mbar_init(cx.afull(0), 1); mbar_init(cx.afull(1), 1);
    mbar_init(cx.afree(0), spare ? 4 : 8); mbar_init(cx.afree(1), 4);
    mbar_init(cx.gbar(), 2); mbar_init(cx.dbar(), 8); mbar_init(cx.cbar(), 2);
    mbar_init(cx.sbar(0), spare ? 4 : 8); mbar_init(cx.sbar(1), spare ? 4 : 8);
#pragma unroll 1
    for (int i = 0; i < 6; i++) mbar_init(cx.fbar(i), 1);
    TSTAMP(491);
    asm volatile("fence.mbarrier_init.release.cluster;" ::: "memory");
    TSTAMP(492);
  } else if (tid == 64) {
    if (!spare && mode != 2) {
      const int i = blockIdx.x - 4;
      l2_prefetch((i & 1 ? wp.wq : wp.wk) + (i >> 1) * 8192, 8192);
    }
    if (!spare && mode != 1) l2_prefetch(wp.wup + (blockIdx.x - 4) * 8192, 8192);
    TSTAMP(493);
    map_prefetch(spare ? &maps.k : &maps.up);
    map_prefetch(spare ? &maps.q : &maps.xs);
    map_prefetch(&maps.xl);
    TSTAMP(494);
  }
  if (threadIdx.x < 256) STAMP(504);
  __syncthreads();
  if (tid == 96) TSTAMP(495);
  cluster_arrive();
  if (threadIdx.x < 256) STAMP(505);

  if (__builtin_expect(warp >= 8, 1)) {
    reg_dealloc<PREG>();
    cluster_wait();
    const uint32_t ro = rank * 16384;
    if (warp == 8) {
      uint32_t si = 0, par = 1, pn = 0;
      auto step = [&](uint32_t w, auto issue) {
        mbar_wait(sb + OFF_BAR + 80 + 8 * si, par);
        const uint32_t fb = sb + OFF_BAR + 40 * w + 8 * si, s = sb + si * SLOT;
        if (elect_one()) { PSTAMP(0, pn); mbar_expect_tx(fb, SLOT); issue(s, fb); PSTAMP(1, pn); }
        pn++;
        if (++si == NS) { si = 0; par ^= 1; }
      };
      if (spare) {
        if (mode != 2) {
#pragma unroll 1
          for (uint32_t n = 0; n < 128; n++) {
            const uint32_t w = (n >> 3) & 1, kb = n & 7, j = n >> 4;
            const CUtensorMap* m = j < 2 ? &maps.k : ((j == 2 || j == 4) ? &maps.ao : &maps.mg);
            const int c1 = j < 2 ? 256 * w + 128 * rank : 64 * kb + (j >= 6 ? 512 : 0), c2 = j < 2 ? kb : 4 * w + 2 * rank;
            step(w, [&](uint32_t s, uint32_t fb) { tma3d_mc(s + ro, m, c1, c2, fb); });
          }
        }
      } else if (mode != 1) {
#pragma unroll 1
        for (uint32_t n = 0; n < 32; n++) {
          const uint32_t w = (n >> 3) & 1;
          step(w, [&](uint32_t s, uint32_t fb) {
            const int c2 = (n < 16 ? 8 : 0) + 4 * w;
            if (n >= NS && (MCM >> (n & 7) & 1)) tma3d_mc(s + ro, &maps.up, 64 * (n & 7), c2 + 2 * rank, fb);
            else { tma3d(s, &maps.up, 64 * (n & 7), c2, fb); tma3d(s + 16384, &maps.up, 64 * (n & 7), c2 + 2, fb); }
          });
        }
#pragma unroll 1
        for (uint32_t n = 0; n < 16; n++) {
          const uint32_t w = n >> 3, kb = n & 7;
          if ((n & 3) == 0) mbar_wait(cx.fbar(n >> 2), 0);
          step(w, [&](uint32_t s, uint32_t fb) {
            const uint8_t* src = g_wqk + kb * TILE + w * SLOT;
            if (MCM >> (n & 7) & 1) bulk_g2s_mc(s + ro, src + ro, 16384, fb); else bulk_g2s(s, src, SLOT, fb);
          });
        }
        mbar_wait(cx.fbar(4), 0);
#pragma unroll 1
        for (uint32_t i = 0; i < 2 * NTILE; i++) {
          const uint32_t t = i >> 1;
          step(t & 1, [&](uint32_t s, uint32_t fb) { tma4d_mc(s + ro, &maps.xl, 64 * t, 4 * ((t ^ i) & 1) + 2 * rank, batch, fb); });
        }
        mbar_wait(cx.fbar(5), 0);
#pragma unroll 1
        for (uint32_t n = 0; n < 32; n++) {
          const uint32_t i = n >> 1, w = n & 1;
          step(w, [&](uint32_t s, uint32_t fb) {
            const uint8_t* src = g_wf + (i < 8 ? i : 8 + ((i + 4 * w) & 7)) * TILE + w * SLOT;
            if (i >= 12) {
              src = g_wf + (12 - 4 * w + 2 * (i & 1)) * TILE + w * SLOT + (i & 2) * 8192;
              bulk_g2s(s, src, 16384, fb); bulk_g2s(s + 16384, src + TILE, 16384, fb);
            } else bulk_g2s(s, src, SLOT, fb);
          });
        }
      }
    } else if (warp == 10) {
      if (lane == 0) {
        if (!spare && mode != 1) {
          const uint32_t ep1 = ld_relaxed(&g_flags[F_DONE * 32]) / NCTA + 1;
#pragma unroll 1
          for (int i = 0; i < 6; i++) {
            wait_flag(i < 4 ? F_WQK + 2 * (i & 1) + (i >> 1) : (i == 4 ? F_XA + batch : F_WF), ep1 * (i < 4 ? 4 : (i == 4 ? 64 : 32)));
            mbar_arrive(cx.fbar(i));
          }
        }
        mbar_wait(cx.dbar(), 0);
      }
    } else if (spare) {
      if (lane == 0 && mode != 2) {
        if (warp == 9) {
          const int s = 2 * cid + rank;
#pragma unroll 1
          for (int rh = 0; rh < 12; rh++) {
            const int r = rh >> 1, h = rh & 1;
            const CUtensorMap* m = r < 2 ? &maps.q : (r < 4 ? &maps.v : &maps.dn);
            const int row = 64 * (s + 4 * (r & 1));
            if (r > 0) mbar_wait(cx.afree(h), (r - 1) & 1);
            mbar_expect_tx(cx.afull(h), SLOT);
            tma3d(sb + OFF_Q + h * SLOT, m, row, 4 * h, cx.afull(h));
            tma3d(sb + OFF_Q + h * SLOT + 16384, m, row, 4 * h + 2, cx.afull(h));
          }
        } else {
#pragma unroll 1
          for (int e = 0; e < 12; e++) {
            mbar_wait(cx.sbar(e & 1), (e >> 1) & 1);
            signal_flag(e < 4 ? F_WQK + e : F_WF);
          }
        }
      }
    } else {
      if (warp == 11) {
        bar_sync_n(3, 288);
        if (lane == 0 && mode != 2) {
#pragma unroll 1
          for (int i = 0; i < 8; i++) {
            tma4d_store(&maps.xs, sb + OFF_Q + i * CH, row0 + 1, i, batch);
            asm volatile("cp.async.bulk.commit_group;" ::: "memory");
            __nanosleep(XPACE);
          }
          const int i = blockIdx.x - 4;
          l2_prefetch(wp.wv + i * 4096, 4096); l2_prefetch(wp.wao + i * 4096, 4096);
          l2_prefetch(wp.wmg + i * 8192, 8192); l2_prefetch(wp.wdn + i * 4096, 4096);
          asm volatile("cp.async.bulk.wait_group 0;" ::: "memory");
          signal_flag(F_XA + batch);
        }
        if (lane == 0 && mode != 1) {
          mbar_wait(cx.sbar(0), 0);
          fence_gpu();
          mbar_arrive(cx.gbar());
          mbar_arrive_cluster(cx.gbar() + cx.pdelta);
        }
        __syncwarp();
      }
      if (mode != 1) {
        const int ch = 4 * (warp >> 1 & 1) + (lane >> 3), lu = lane & 7;
        uint32_t dk[3][4];
#pragma unroll
        for (int k = 0; k < 3; k++)
#pragma unroll
          for (int jj = 0; jj < 4; jj++) dk[k][jj] = __ldg((const uint32_t*)dw + 256 * k + 32 * ch + 16 * (lu >> 2) + 4 * jj + (lu & 3));
        mbar_wait_cl(cx.gbar(), 0);
        mbar_wait(cx.sbar(1), 0);
        uint8_t* up_ = g_uc + (size_t)(2 * pairi) * TILE + ch * CH;
        const float4* sp_ = (const float4*)g_st + pairi * 128;
        uint32_t p1[4] = {0, 0, 0, 0}, p2[4] = {0, 0, 0, 0};
        uint32_t oo = 0;
#pragma unroll 1
        for (int L = 64 * (int)rank - 1; L <= 64 * (int)rank + (NOCONV ? -2 : 64); L++) {
          const uint32_t Lc = min(max(L, 0), 127), oc = (Lc >> 6) * TILE + (Lc & 63) * 128 + ((lu ^ (Lc & 7)) << 4);
          const uint4 g = __ldcg((const uint4*)(up_ + 128 * TILE + oc));
          const float4 st = __ldcg(sp_ + Lc);
          uint4* uo = (uint4*)(up_ + oo);
          const uint4 u = __ldcg(uo);
          oo = oc;
          const float mu_ = (st.x + st.z) * (1.f / DD);
          const float r = rsqrtf(fmaxf(fmaf(-mu_, mu_, (st.y + st.w) * (1.f / DD)), 0.f) + 1e-5f), m = -mu_ * r;
          const uint32_t gg[4] = {g.x, g.y, g.z, g.w}, uu[4] = {u.x, u.y, u.z, u.w};
          uint32_t o[4];
#pragma unroll
          for (int jj = 0; jj < 4; jj++) {
            const uint32_t gn = pack2(fmaf(blo(gg[jj]), r, m), fmaf(bhi(gg[jj]), r, m));
            o[jj] = hmul2(uu[jj], hfma2(gn, dk[2][jj], p1[jj]));
            p1[jj] = hfma2(gn, dk[1][jj], p2[jj]);
            p2[jj] = hmul2(gn, dk[0][jj]);
          }
          if (L > 64 * (int)rank) __stcg(uo, make_uint4(o[0], o[1], o[2], o[3]));
        }
        __syncwarp();
        if (lane == 0) mbar_arrive(cx.cbar());
        if (lane == 0 && warp == 9) {
          const uint8_t* uc = g_uc + (size_t)(2 * pairi + rank) * TILE;
          mbar_wait(cx.cbar(), 0);
#pragma unroll 1
          for (int h = 0; h < 2; h++) {
            mbar_wait(cx.afree(h), 0);
            if (h == 0) {
              const int r0 = max(row0, 0), r1 = min(row0 + 64, TT);
              l2_prefetch(x + ((size_t)batch * TT + r0) * DD, (r1 - r0) * DD * 2);
            }
            fence_async_all();
            mbar_expect_tx(cx.afull(h), h ? CH : 7 * CH);
            bulk_g2s(sb + OFF_Q + h * 7 * CH, uc + h * 7 * CH, h ? CH : 7 * CH, cx.afull(h));
          }
        }
      }
    }
    __syncwarp();
    cluster_arrive();
    cluster_wait();
  } else {
    reg_alloc<CREG>();
    STAMP(0); GSTAMP(500);
    const int w = warp >> 2, wq = warp & 3, q = lane >> 2, c = lane & 3;
    cx.fb = cx.full(0, w); cx.ph = 0; cx.l0 = lane == 0;
    const int rlo = 16 * wq + q;
    const int mrow = 16 * wq + (lane & 15);
    const uint32_t moff = mrow * 128, mx = mrow & 7, mu = lane >> 4;
    float acc[128];

    if (spare) {
      cluster_wait();
      if (mode != 2) {
        const int s = 2 * cid + rank;
        int ar = 0;
#pragma unroll 1
        for (int j = 0; j < 8; j++) {
          MARK(mode * 1000 + j * 10); STAMP(1 + 2 * j);
          const bool tmaA = (j != 3 && j != 5), t1 = (j == 2 || j == 4), nextTma = (j != 2 && j != 4 && j != 7);
          auto pre = [&](int kb) {
            if (tmaA && (kb & 3) == 0) mbar_wait(cx.afull(kb >> 2), ar & 1);
            if (!tmaA && kb == (w ? 0 : 4)) bar_sync(w ? 5 : 6);
          };
          auto post = [&](int kb) {
            if (w == 1 && (kb & 3) == 3) {
              if (nextTma) { if (lane == 0) mbar_arrive(cx.afree(kb >> 2)); }
              else if (t1 && kb == 3) bar_arrive(4);
            }
          };
          if (j < 2) gemm8<0, 0>(cx, acc, 16 * j + 8 * w, pre, post);
          else gemm8<1, 0>(cx, acc, 16 * j + 8 * w, pre, post);
          MARK(mode * 1000 + j * 10 + 1); STAMP(2 + 2 * j);
          if (tmaA) ar++;
          const float sc = j < 2 ? 4.f * 0.04419417382415922f * 1.4426950408889634f : 1.f;
          uint32_t pk[64];
#pragma unroll
          for (int i = 0; i < 64; i++) pk[i] = pack2(acc[2 * i] * sc, acc[2 * i + 1] * sc);
          if (t1) {
            if (w == 0) bar_sync(4);
#pragma unroll
            for (int ks = 0; ks < 16; ks++)
              stsm4(sb + OFF_Q + (4 * w + (ks >> 2)) * CH + moff + (((2 * (ks & 3) + mu) ^ mx) << 4), pk[4 * ks], pk[4 * ks + 1], pk[4 * ks + 2], pk[4 * ks + 3]);
            fence_async_smem();
            bar_arrive(w ? 6 : 5);
          } else {
            const int blk = s + 4 * (j < 2 ? j : (j < 6 ? (j >> 2) : (j & 1)));
            uint8_t* dst = (j < 2 ? g_wqk + blk * TILE : g_wf + (j < 6 ? 8 + blk : blk) * TILE) + 4 * w * CH;
            const int r0 = j >= 6 ? sigma(rlo) : rlo, r1 = j >= 6 ? sigma(rlo + 8) : rlo + 8;
            uint8_t* d0 = dst + r0 * 128, * d1 = dst + r1 * 128;
#pragma unroll
            for (int i = 0; i < 8; i++) {
              const int u = 4 * (i & 1) + c;
              *(uint4*)(d0 + (i >> 1) * CH + ((u ^ (r0 & 7)) << 4)) = make_uint4(pk[8 * i], pk[8 * i + 2], pk[8 * i + 4], pk[8 * i + 6]);
              *(uint4*)(d1 + (i >> 1) * CH + ((u ^ (r1 & 7)) << 4)) = make_uint4(pk[8 * i + 1], pk[8 * i + 3], pk[8 * i + 5], pk[8 * i + 7]);
            }
            __syncwarp();
            if (lane == 0) mbar_arrive(cx.sbar(w));
          }
        }
      }
    } else {
      {
#pragma unroll 1
        for (int h = -1; h < 2; h++) {
          const uint32_t r = 4 * max(h, 0) + (lane >> 3), a = sb + OFF_Q + (8 * warp + r) * 128 + (((lane & 7) ^ r) << 4);
          if (h == 0) { mbar_wait(cx.xbar(), 0); STAMP(300); }
          uint32_t v[8][4];
#pragma unroll
          for (int i = 0; i < 8; i++) lds128(a + i * CH, v[i]);
          const float sh = blo(__shfl_sync(~0u, v[0][0], lane & 24));
          float s1 = 0.f, s2 = 0.f, t1 = 0.f, t2 = 0.f;
#pragma unroll
          for (int i = 0; i < 8; i++)
#pragma unroll
            for (int k = 0; k < 4; k++) {
              const float d = blo(v[i][k]) - sh, e = bhi(v[i][k]) - sh;
              s1 += d; s2 = fmaf(d, d, s2); t1 += e; t2 = fmaf(e, e, t2);
            }
          s1 += t1; s2 += t2;
#pragma unroll
          for (int o = 1; o < 8; o <<= 1) { s1 += __shfl_xor_sync(~0u, s1, o); s2 += __shfl_xor_sync(~0u, s2, o); }
          s1 *= (1.f / DD);
          const float rs = 0.5f * rsqrtf(fmaxf(fmaf(-s1, s1, s2 * (1.f / DD)), 0.f) + 1e-5f), mr = -(sh + s1) * rs;
#pragma unroll
          for (int i = 0; i < 8; i++) {
#pragma unroll
            for (int k = 0; k < 4; k++) v[i][k] = pack2(fmaf(blo(v[i][k]), rs, mr), fmaf(bhi(v[i][k]), rs, mr));
            asm volatile("{\n.reg .pred p;\nsetp.ge.s32 p, %5, 0;\n@p st.shared.v4.b32 [%0], {%1, %2, %3, %4};\n}\n"
                         :: "r"(a + i * CH), "r"(v[i][0]), "r"(v[i][1]), "r"(v[i][2]), "r"(v[i][3]), "r"(h) : "memory");
          }
          if (h == 0) STAMP(301);
        }
        STAMP(302);
        fence_async_smem();
      }
      cluster_wait();
      MARK(510); STAMP(1);
      bar_sync_n(3, 288);
      if (mode != 1) {
        MARK(511); STAMP(2);
        uint32_t qf[16];
#pragma unroll 1
        for (int ph = 0; ph < 3; ph++) {
          gemm8<1, N_ATT0 - NS>(cx, acc, 16 * ph + 8 * w, [](int) {}, [&](int kb) { if (ph == 2 && w == 1 && kb == 3) bar_arrive(4); });
          MARK(512 + 2 * ph); STAMP(3 + 2 * ph);
          if (ph < 2) {
            float s1a = 0.f, s2a = 0.f, s1b = 0.f, s2b = 0.f;
            uint8_t* d = g_uc + (size_t)(2 * pairi + rank + (ph ? 0 : 128)) * TILE + 4 * w * CH + rlo * 128;
#pragma unroll
            for (int i = 0; i < 8; i++) {
              uint32_t pa[4], pb[4];
#pragma unroll
              for (int jj = 0; jj < 4; jj++) {
                const int j = 4 * i + jj;
                const float a0 = gelu2(acc[4 * j]), a1 = gelu2(acc[4 * j + 1]), b0 = gelu2(acc[4 * j + 2]), b1 = gelu2(acc[4 * j + 3]);
                acc[4 * j] = a0; acc[4 * j + 1] = a1; acc[4 * j + 2] = b0; acc[4 * j + 3] = b1;
                pa[jj] = pack2(a0, a1); pb[jj] = pack2(b0, b1);
              }
              uint8_t* e = d + (i >> 1) * CH + (((4 * (i & 1) + c) ^ q) << 4);
              STG((uint4*)e, make_uint4(pa[0], pa[1], pa[2], pa[3]));
              STG((uint4*)(e + 1024), make_uint4(pb[0], pb[1], pb[2], pb[3]));
            }
            STAMP(310 + ph);
            if (ph == 0) {
#pragma unroll
              for (int j = 0; j < 32; j++) {
                s1a += acc[4 * j] + acc[4 * j + 1]; s2a = fmaf(acc[4 * j], acc[4 * j], s2a); s2a = fmaf(acc[4 * j + 1], acc[4 * j + 1], s2a);
                s1b += acc[4 * j + 2] + acc[4 * j + 3]; s2b = fmaf(acc[4 * j + 2], acc[4 * j + 2], s2b); s2b = fmaf(acc[4 * j + 3], acc[4 * j + 3], s2b);
              }
#pragma unroll
              for (int o = 1; o < 4; o <<= 1) {
                s1a += __shfl_xor_sync(~0u, s1a, o); s2a += __shfl_xor_sync(~0u, s2a, o);
                s1b += __shfl_xor_sync(~0u, s1b, o); s2b += __shfl_xor_sync(~0u, s2b, o);
              }
              float2* sp = g_st + ((2 * pairi + rank) * 64 + rlo) * 2 + w;
              if (c == 0) { __stcg(sp, make_float2(s1a, s2a)); __stcg(sp + 16, make_float2(s1b, s2b)); }
            }
            __syncwarp();
            if (lane == 0) mbar_arrive(cx.sbar(ph));
          } else {
            mbar_wait(cx.gbar(), 0);
            if (w == 0) bar_sync(4);
#pragma unroll
            for (int i = 0; i < 8; i++) {
              const uint32_t a = sb + OFF_Q + (4 * w + (i >> 1)) * CH + rlo * 128 + (((4 * (i & 1) + c) ^ q) << 4);
              sts128(a, pack2(acc[16 * i], acc[16 * i + 1]), pack2(acc[16 * i + 4], acc[16 * i + 5]), pack2(acc[16 * i + 8], acc[16 * i + 9]), pack2(acc[16 * i + 12], acc[16 * i + 13]));
              sts128(a + 1024, pack2(acc[16 * i + 2], acc[16 * i + 3]), pack2(acc[16 * i + 6], acc[16 * i + 7]), pack2(acc[16 * i + 10], acc[16 * i + 11]), pack2(acc[16 * i + 14], acc[16 * i + 15]));
            }
            fence_async_smem();
            bar_sync_n(12 + w, 128);
          }
          MARK(513 + 2 * ph); STAMP(4 + 2 * ph);
        }
        if (w == 1) {
#pragma unroll
          for (int ks = 0; ks < 4; ks++) ldsm4(sb + OFF_P + moff + (((2 * ks + mu) ^ mx) << 4), qf[4 * ks], qf[4 * ks + 1], qf[4 * ks + 2], qf[4 * ks + 3]);
        }
        bar_arrive(w ? 6 : 5);

        float m0 = -INFINITY, m1 = -INFINITY, l0 = 0.f, l1 = 0.f;
        const uint32_t exa = sb + OFF_EX + (tid & 127) * 16;
        const uint32_t dq = desc_k(sb + OFF_Q), dp = desc_k(sb + OFF_P), dk0 = desc_k(sb), dv = desc_mn(sb), eb = cx.empty(0);
        const uint32_t pw = sb + OFF_P + moff;
        float S[32];
        uint32_t P[16];
        float f0, f1, i0, i1;
        zero_regs(acc);
        auto rescale = [&]() {
#pragma unroll
          for (int j = 0; j < 32; j++) { acc[4 * j] *= f0; acc[4 * j + 1] *= f0; acc[4 * j + 2] *= f1; acc[4 * j + 3] *= f1; }
        };
        auto recv_px = [&](uint32_t sl, bool live, int kmax) {
          bar_sync(2 - w);
          float a, b;
          asm volatile("ld.shared.v4.f32 {%0, %1, %2, %3}, [%4];" : "=f"(a), "=f"(b), "=f"(l0), "=f"(l1) : "r"(exa) : "memory");
          if (__builtin_expect(live && __any_sync(~0u, a != m0 || b != m1), 0)) { f0 = ex2(m0 - a); f1 = ex2(m1 - b); rescale(); }
          m0 = a; m1 = b;
          const uint32_t db = dv + sl * (SLOT >> 4);
          wg_fence();
#pragma unroll
          for (int k = 0; k < 4; k++) if (k < kmax) wgmma_ss_n256_tb1(acc, dp + k * 2, db + k * 128, 1);
        };
        auto qk_lo = [&](uint32_t sl, int k0, int k1) {
          const uint32_t dk = dk0 + sl * (SLOT >> 4);
          wg_fence();
#pragma unroll
          for (int k = 0; k < 16; k++)
            if (k >= k0 && k < k1) wgmma_ss_n64_tb0(S, dq + (k >> 2) * 512 + (k & 3) * 2, dk + (k >> 2) * 512 + (k & 3) * 2, 1);
          wg_commit();
        };
        auto qk_hi = [&](uint32_t sl, int k0, int k1) {
          const uint32_t dk = dk0 + sl * (SLOT >> 4);
          wg_fence();
#pragma unroll
          for (int k = 0; k < 12; k++)
            if (k >= k0 && k < k1) wgmma_ss_n64_tb0(S, dq + 2048 + (k >> 2) * 512 + (k & 3) * 2, dk + (k >> 2) * 512 + (k & 3) * 2, 1);
#pragma unroll
          for (int k = 0; k < 4; k++)
            if (k1 == 16) wgmma_rs_n64_tb0(S, qf[4 * k], qf[4 * k + 1], qf[4 * k + 2], qf[4 * k + 3], dk + 1536 + k * 2, 1);
          wg_commit();
        };
        auto expsum = [&](float d0, float d1, float& s0, float& s1, bool sub, int j0, int j1) {
#pragma unroll
          for (int j = j0; j < j1; j++) {
            float a0 = ex2(sub ? S[4 * j] - d0 : S[4 * j]), a1 = ex2(sub ? S[4 * j + 1] - d0 : S[4 * j + 1]);
            float b0 = ex2(sub ? S[4 * j + 2] - d1 : S[4 * j + 2]), b1 = ex2(sub ? S[4 * j + 3] - d1 : S[4 * j + 3]);
            s0 += a0 + a1; s1 += b0 + b1;
            P[2 * j] = pack2(a0, a1); P[2 * j + 1] = pack2(b0, b1);
          }
        };
        auto softmax = [&]() -> bool {
          float s0 = 0.f, s1 = 0.f;
          expsum(0.f, 0.f, s0, s1, false, 0, 8);
          bool chg = false;
          if (__builtin_expect(__any_sync(~0u, s0 > PMAX || s1 > PMAX || m0 != i0 || m1 != i1), 0)) {
            float x0 = fmaxf(S[0], S[1]), x1 = fmaxf(S[2], S[3]);
#pragma unroll
            for (int j = 1; j < 8; j++) { x0 = fmaxf(x0, fmaxf(S[4 * j], S[4 * j + 1])); x1 = fmaxf(x1, fmaxf(S[4 * j + 2], S[4 * j + 3])); }
            x0 = fmaxf(x0, __shfl_xor_sync(~0u, x0, 1)); x1 = fmaxf(x1, __shfl_xor_sync(~0u, x1, 1));
            x0 = fmaxf(x0, __shfl_xor_sync(~0u, x0, 2)); x1 = fmaxf(x1, __shfl_xor_sync(~0u, x1, 2));
            x0 += i0; x1 += i1;
            chg = __any_sync(~0u, x0 > m0 + 6.f || x1 > m1 + 6.f);
            if (chg) {
              x0 = fmaxf(x0, m0); x1 = fmaxf(x1, m1);
              f0 = ex2(m0 - x0); f1 = ex2(m1 - x1);
              m0 = x0; m1 = x1;
              l0 *= f0; l1 *= f1;
            }
            s0 = 0.f; s1 = 0.f;
            expsum(m0 - i0, m1 - i1, s0, s1, true, 0, 8);
          }
          l0 += s0; l1 += s1;
          return chg;
        };
        auto sinit = [&](bool first) {
          i0 = first ? 0.f : m0; i1 = first ? 0.f : m1;
#pragma unroll
          for (int j = 0; j < 8; j++) { S[4 * j] = -i0; S[4 * j + 1] = -i0; S[4 * j + 2] = -i1; S[4 * j + 3] = -i1; }
          fence_regs(S);
        };
        auto send = [&]() {
#pragma unroll
          for (int ks = 0; ks < 4; ks++) stsm4(pw + (((2 * ks + mu) ^ mx) << 4), P[4 * ks], P[4 * ks + 1], P[4 * ks + 2], P[4 * ks + 3]);
          asm volatile("st.shared.v4.f32 [%0], {%1, %2, %3, %4};" :: "r"(exa), "f"(m0), "f"(m1), "f"(l0), "f"(l1) : "memory");
          fence_async_smem();
          bar_arrive(1 + w);
        };
        auto po = [&](uint32_t sl) {
          const uint32_t db = dv + sl * (SLOT >> 4);
          wg_fence();
#pragma unroll
          for (int k = 0; k < 4; k++) wgmma_rs_n256_tb1(acc, P[4 * k], P[4 * k + 1], P[4 * k + 2], P[4 * k + 3], db + k * 128, 1);
          wg_commit();
        };
        if (w == 1) bar_sync(5);
        uint32_t s0 = (N_ATT0 + 2 * w) % NS, s1 = (N_ATT0 + 2 * w + 1) % NS, sm = (N_ATT0 + 2 * w - 1) % NS;
#pragma unroll 1
        for (int t = w; t < NTILE; t += 2) {
          MARK(600 + t); FSTAMP(32 + (t >> 1) * 8);
          sinit(t < 2);
          const uint32_t e1 = eb + 8 * s1, em = eb + 8 * sm, em2 = em + (MCF || t < NTILE - 2 ? cx.pdelta : 0);
          const uint32_t fb1 = cx.fb + 8 * s1, par1 = (cx.ph >> s1) & 1;
          mbar_wait(cx.fb + 8 * s0, (cx.ph >> s0) & 1);
          cx.ph ^= (1u << s0) | (1u << s1);
          {
            const uint32_t da = dq + w * 2048, dk = dk0 + s0 * (SLOT >> 4);
            wg_fence();
#pragma unroll
            for (int k = 0; k < QKA; k++) wgmma_ss_n64_tb0(S, da + (k >> 2) * 512 + (k & 3) * 2, dk + (k >> 2) * 512 + (k & 3) * 2, 1);
            wg_commit();
          }
          wg_wait<1>();
          fence_regs(acc);
          fence_regs(P);
          arrive2(e1, e1 + cx.pdelta, cx.l0 && t >= 2);
          if (w == 0) qk_lo(s0, QKA, 16); else qk_hi(s0, QKA, 16);
          if (t == 0) {
            bar_sync(6);
#pragma unroll
            for (int ks = 0; ks < 4; ks++) ldsm4(pw + (((2 * ks + mu) ^ mx) << 4), qf[4 * ks], qf[4 * ks + 1], qf[4 * ks + 2], qf[4 * ks + 3]);
          }
          FSTAMP(33 + (t >> 1) * 8);
          mbar_wait(fb1, par1);
          if (w == 0) qk_hi(s1, 0, 16); else qk_lo(s1, 0, 16);
          FSTAMP(34 + (t >> 1) * 8);
          if (t > 0) {
            recv_px(sm, t > 1, 4);
            wg_commit();
            wg_wait<1>();
          } else {
            wg_wait<0>();
          }
          fence_regs(S);
          FSTAMP(35 + (t >> 1) * 8);
          if (t >= NTILE - 2) {
            if (lane == 0) mbar_arrive(cx.afree(0));
            if (t == NTILE - 1) {
#pragma unroll
              for (int i = 16; i < 32; i++) S[i] = -INFINITY;
            }
          }
          const bool chg = softmax();
          FSTAMP(36 + (t >> 1) * 8);
          wg_wait<0>();
          fence_regs(acc);
          FSTAMP(37 + (t >> 1) * 8);
          arrive2(em, em2, cx.l0 && t > 0);
          if (__builtin_expect(chg && t > 0, 0)) rescale();
          po(s0);
          FSTAMP(38 + (t >> 1) * 8);
          send();
          FSTAMP(39 + (t >> 1) * 8);
          s1 = s0; s0 = sm; sm = sm ? sm - 1 : NS - 1;
        }
        wg_wait<0>();
        fence_regs(acc);
        cx.release(N_ATT0 + 2 * (NTILE - 1 - w));
        if (w == 1) {
          const uint32_t n = N_ATT0 + 2 * (NTILE - 1) + 1;
          recv_px(n % NS, true, 4);
          wg_commit();
          wg_wait<0>();
          fence_regs(acc);
          cx.release(n);
          if (lane == 0) mbar_arrive(cx.afree(1));
        }
        STAMP(9);
        l0 += __shfl_xor_sync(~0u, l0, 1); l1 += __shfl_xor_sync(~0u, l1, 1);
        l0 += __shfl_xor_sync(~0u, l0, 2); l1 += __shfl_xor_sync(~0u, l1, 2);
        uint32_t gp[64];
        {
          const float r0 = 2.f * __frcp_rn(l0), r1 = 2.f * __frcp_rn(l1);
#pragma unroll
          for (int j = 0; j < 32; j++) { gp[2 * j] = pack2(acc[4 * j] * r0, acc[4 * j + 1] * r0); gp[2 * j + 1] = pack2(acc[4 * j + 2] * r1, acc[4 * j + 3] * r1); }
        }
        const int La = 64 * (int)rank + rlo, Lb = La + 8;
        const bool va = La >= 1 && La <= 125, vb = Lb <= 125;
        const size_t goff = ((size_t)batch * TT + row0 + rlo) * DD + 256 * w + 8 * c;
        STAMP(10);
        zero_regs(acc);
        uint32_t sl = (N_FIN0 + w) % NS, e = 0, fb = cx.fb + 8 * sl, par = (cx.ph >> sl) & 1, db = dv + sl * (SLOT >> 4);
        auto next = [&](bool rel) {
          const uint32_t pe = e;
          e = eb + 8 * sl;
          cx.ph ^= 1u << sl;
          sl = sl >= NS - 2 ? sl - (NS - 2) : sl + 2;
          fb = cx.fb + 8 * sl; par = (cx.ph >> sl) & 1; db = dv + sl * (SLOT >> 4);
          wg_wait<1>();
          arrive2(pe, pe + (MCF ? cx.pdelta : 0), cx.l0 && rel);
        };
        uint32_t xr[64];
        auto resid = [&](int i0) {
#pragma unroll
          for (int i = i0; i < i0 + 4; i++) {
            const uint4 u = va ? __ldg((const uint4*)(x + goff + 32 * i)) : make_uint4(0, 0, 0, 0);
            const uint4 v = vb ? __ldg((const uint4*)(x + goff + 8 * DD + 32 * i)) : make_uint4(0, 0, 0, 0);
            xr[8 * i] = u.x; xr[8 * i + 1] = u.y; xr[8 * i + 2] = u.z; xr[8 * i + 3] = u.w;
            xr[8 * i + 4] = v.x; xr[8 * i + 5] = v.y; xr[8 * i + 6] = v.z; xr[8 * i + 7] = v.w;
          }
        };
        auto ss = [&](uint32_t da, bool rel) {
          mbar_wait(fb, par);
          wg_fence();
#pragma unroll
          for (int k = 0; k < 4; k++) wgmma_ss_n256_tb1(acc, da + k * 2, db + k * 128, 1);
          wg_commit();
          next(rel);
        };
#pragma unroll 1
        for (int kb = 0; kb < 8; kb++) {
          if (kb == 0 || kb == 7) mbar_wait(cx.afull(kb & 1), 0);
          ss(dq + kb * (CH >> 4), kb > 0);
        }
        STAMP(11);
#pragma unroll
        for (int kb = 0; kb < 4; kb++) {
          mbar_wait(fb, par);
          wg_fence();
#pragma unroll
          for (int k = 0; k < 4; k++) wgmma_rs_n256_tb1(acc, gp[16 * kb + 4 * k], gp[16 * kb + 4 * k + 1], gp[16 * kb + 4 * k + 2], gp[16 * kb + 4 * k + 3], db + k * 128, 1);
          wg_commit();
          next(true);
          if (kb == 0) bar_arrive(7 + w);
          if (kb == 1) {
            bar_sync(8 - w);
#pragma unroll
            for (int ks = 0; ks < 16; ks++)
              stsm4(sb + OFF_Q + (4 * w + (ks >> 2)) * CH + moff + (((2 * (ks & 3) + mu) ^ mx) << 4), gp[4 * ks], gp[4 * ks + 1], gp[4 * ks + 2], gp[4 * ks + 3]);
            fence_async_smem();
            bar_arrive(9 + w);
          }
        }
        STAMP(12);
        bar_sync(10 - w);
        STAMP(13);
        auto half = [&](auto o, uint32_t da, bool last = false) {
          mbar_wait(fb, par);
          wg_fence();
#pragma unroll
          for (int k = 0; k < 8; k++) wgmma_ss_n128_tb1<o.value>(acc, da + (k >> 2) * (CH >> 4) + (k & 3) * 2, db + (k >> 2) * 1024 + (k & 3) * 128, 1);
          wg_commit();
          if (!last) next(true);
        };
        auto fin = [&](int i0, int i1) {
#pragma unroll
          for (int j = 16 * i0; j < 16 * i1; j++) asm volatile("" : "+f"(acc[j]) :: "memory");
#pragma unroll
          for (int i = i0; i < i1; i++) {
            const uint32_t* a = &xr[8 * i];
            const uint32_t* b = &xr[8 * i + 4];
            uint4 oa, ob;
            oa.x = pack2(acc[16 * i] + blo(a[0]), acc[16 * i + 1] + bhi(a[0])); oa.y = pack2(acc[16 * i + 4] + blo(a[1]), acc[16 * i + 5] + bhi(a[1]));
            oa.z = pack2(acc[16 * i + 8] + blo(a[2]), acc[16 * i + 9] + bhi(a[2])); oa.w = pack2(acc[16 * i + 12] + blo(a[3]), acc[16 * i + 13] + bhi(a[3]));
            ob.x = pack2(acc[16 * i + 2] + blo(b[0]), acc[16 * i + 3] + bhi(b[0])); ob.y = pack2(acc[16 * i + 6] + blo(b[1]), acc[16 * i + 7] + bhi(b[1]));
            ob.z = pack2(acc[16 * i + 10] + blo(b[2]), acc[16 * i + 11] + bhi(b[2])); ob.w = pack2(acc[16 * i + 14] + blo(b[3]), acc[16 * i + 15] + bhi(b[3]));
            if (va) *(uint4*)(out + goff + 32 * i) = oa;
            if (vb) *(uint4*)(out + goff + 8 * DD + 32 * i) = ob;
          }
        };
        const uint32_t dpa = dq + 4 * (1 - w) * (CH >> 4);
        wg_wait<0>();
        fence_regs(gp);
#pragma unroll
        for (int j = 0; j < 128; j++) { float t; asm volatile("mov.b32 %0, %1;" : "=f"(t) : "f"(acc[j]) : "memory"); acc[j] = t; }
        half(IC<0>(), dpa);
        resid(0);
        half(IC<0>(), dpa + 2 * (CH >> 4));
        resid(4);
        half(IC<64>(), dpa);
        fin(0, TSPLIT);
        half(IC<64>(), dpa + 2 * (CH >> 4), true);
        fin(TSPLIT, 4);
        wg_wait<0>();
        STAMP(14);
        fin(4, 8);
      }
    }
    MARK(mode * 1000 + 999); STAMP(20); GSTAMP(501);
    if (lane == 0) mbar_arrive(cx.dbar());
    if (tid == 0 && mode != 1) atomicAdd(&g_flags[F_DONE * 32], 1u);
    __syncwarp();
    cluster_arrive();
    cluster_wait();
  }
}

typedef CUresult (*EncodeFn)(CUtensorMap*, CUtensorMapDataType, cuuint32_t, void*, const cuuint64_t*, const cuuint64_t*, const cuuint32_t*,
                             const cuuint32_t*, CUtensorMapInterleave, CUtensorMapSwizzle, CUtensorMapL2promotion, CUtensorMapFloatOOBfill);

static void make_map(EncodeFn fn, CUtensorMap* m, void* p, int rows, int cols, int box_rows, int box_blks) {
  cuuint64_t dims[3] = {64, (cuuint64_t)rows, (cuuint64_t)(cols / 64)};
  cuuint64_t strides[2] = {(cuuint64_t)cols * 2, 128};
  cuuint32_t box[3] = {64, (cuuint32_t)box_rows, (cuuint32_t)box_blks};
  cuuint32_t es[3] = {1, 1, 1};
  fn(m, CU_TENSOR_MAP_DATA_TYPE_BFLOAT16, 3, p, dims, strides, box, es, CU_TENSOR_MAP_INTERLEAVE_NONE, CU_TENSOR_MAP_SWIZZLE_128B,
     CU_TENSOR_MAP_L2_PROMOTION_L2_256B, CU_TENSOR_MAP_FLOAT_OOB_FILL_NONE);
}

static void make_map4(EncodeFn fn, CUtensorMap* m, void* p, int rows, int brows, int box_blks) {
  cuuint64_t dims[4] = {64, (cuuint64_t)rows, 8, 2};
  cuuint64_t strides[3] = {DD * 2, 128, (cuuint64_t)brows * DD * 2};
  cuuint32_t box[4] = {64, 64, (cuuint32_t)box_blks, 1};
  cuuint32_t es[4] = {1, 1, 1, 1};
  fn(m, CU_TENSOR_MAP_DATA_TYPE_BFLOAT16, 4, p, dims, strides, box, es, CU_TENSOR_MAP_INTERLEAVE_NONE, CU_TENSOR_MAP_SWIZZLE_128B,
     CU_TENSOR_MAP_L2_PROMOTION_L2_256B, CU_TENSOR_MAP_FLOAT_OOB_FILL_NONE);
}

}

extern "C" void kernel_launch(void* const* d_in, const int* in_sizes, int n_in, void* d_out, int out_size) {
  using namespace bf;
  static EncodeFn fn = nullptr;
  static int fused = 0;
  static void* xa_ptr = nullptr;
  if (!fn) {
    void* p = nullptr;
    cudaDriverEntryPointQueryResult qr;
    cudaGetDriverEntryPoint("cuTensorMapEncodeTiled", &p, cudaEnableDefault, &qr);
    fn = (EncodeFn)p;
    cudaGetSymbolAddress(&xa_ptr, g_xa);
    cudaFuncSetAttribute(bf_kernel, cudaFuncAttributeMaxDynamicSharedMemorySize, SMEM_BYTES);
    cudaLaunchConfig_t cfg = {};
    cfg.gridDim = dim3(NCTA); cfg.blockDim = dim3(384); cfg.dynamicSmemBytes = SMEM_BYTES;
    cudaLaunchAttribute at[1];
    at[0].id = cudaLaunchAttributeClusterDimension; at[0].val.clusterDim.x = 2; at[0].val.clusterDim.y = 1; at[0].val.clusterDim.z = 1;
    cfg.attrs = at; cfg.numAttrs = 1;
    int nc = 0;
    cudaOccupancyMaxActiveClusters(&nc, bf_kernel, &cfg);
    fused = nc >= NCTA / 2;
  }
  Maps maps;
  make_map(fn, &maps.q, d_in[1], 512, 512, 64, 2);
  make_map(fn, &maps.k, d_in[2], 512, 512, 128, 1);
  make_map(fn, &maps.v, d_in[3], 512, 512, 64, 2);
  make_map(fn, &maps.ao, d_in[4], 512, 512, 64, 2);
  make_map(fn, &maps.up, d_in[5], 512, 1024, 64, 2);
  make_map(fn, &maps.dn, d_in[7], 512, 512, 64, 2);
  make_map(fn, &maps.mg, d_in[8], 1024, 512, 64, 2);
  make_map4(fn, &maps.x, d_in[0], TT, TT, 4);
  make_map4(fn, &maps.xs, xa_ptr, TT + 1, TT + 1, 1);
  make_map4(fn, &maps.xl, (uint8_t*)xa_ptr + DD * 2, TT, TT + 1, 2);
  Ptrs wp = {(const uint8_t*)d_in[1], (const uint8_t*)d_in[2], (const uint8_t*)d_in[3], (const uint8_t*)d_in[4],
             (const uint8_t*)d_in[5], (const uint8_t*)d_in[7], (const uint8_t*)d_in[8]};
  const __nv_bfloat16* x = (const __nv_bfloat16*)d_in[0];
  const __nv_bfloat16* dw = (const __nv_bfloat16*)d_in[6];
  __nv_bfloat16* out = (__nv_bfloat16*)d_out;
  if (fused) {
    bf_kernel<<<NCTA, 384, SMEM_BYTES>>>(maps, wp, x, dw, out, 0);
  } else {
    bf_kernel<<<NCTA, 384, SMEM_BYTES>>>(maps, wp, x, dw, out, 1);
    bf_kernel<<<NCTA, 384, SMEM_BYTES>>>(maps, wp, x, dw, out, 2);
  }
}
```

```cpp
#include <cuda_runtime.h>
#include <cuda_bf16.h>
#include <cuda.h>
#include <stdint.h>

namespace bf {

constexpr int TT = 4000, DD = 512, NTILE = 63;
constexpr uint32_t CH = 8192, SLOT = 32768, NS = 5, TILE = 65536;
constexpr uint32_t OFF_Q = NS * SLOT;
constexpr uint32_t OFF_P = OFF_Q + 7 * CH;
constexpr uint32_t OFF_EX = OFF_Q + TILE;
constexpr uint32_t OFF_BAR = OFF_EX + 2048;
constexpr uint32_t SMEM_BYTES = OFF_BAR + 256;
constexpr int NCTA = 132;
#define QKA 3
#define CREG 224
#define PREG 56
#define STO(p, v) __stcs(p, v)
#define TSPLIT 4
#define XPACE 150
#define STG(p, v) __stcg(p, v)
#define NOCONV 0
#define MCM 0x00
#define MCF 0
#define PMAX 1024.f
constexpr uint32_t N_ATT0 = 48, N_FIN0 = 48 + 2 * NTILE;

struct Maps { CUtensorMap x, up, q, k, xs, xl, v, ao, dn, mg; };
struct Ptrs { const uint8_t *wq, *wk, *wv, *wao, *wup, *wdn, *wmg; };

__device__ __align__(1024) uint8_t g_xa[2 * (TT + 1) * DD * 2];
__device__ __align__(1024) uint8_t g_uc[256 * TILE];
__device__ __align__(1024) uint8_t g_wqk[8 * TILE];
__device__ __align__(1024) uint8_t g_wf[16 * TILE];
__device__ __align__(1024) float2 g_st[128 * 64 * 2];
__device__ uint32_t g_flags[8 * 32];
constexpr int F_WQK = 0, F_XA = 4, F_WF = 6, F_DONE = 7;

__device__ __forceinline__ uint32_t smem_u32(const void* p) { return (uint32_t)__cvta_generic_to_shared(p); }
__device__ __forceinline__ void mbar_init(uint32_t bar, uint32_t cnt) { asm volatile("mbarrier.init.shared::cta.b64 [%0], %1;" :: "r"(bar), "r"(cnt)); }
__device__ __forceinline__ void mbar_expect_tx(uint32_t bar, uint32_t bytes) { asm volatile("mbarrier.arrive.expect_tx.shared::cta.b64 _, [%0], %1;" :: "r"(bar), "r"(bytes) : "memory"); }
__device__ __forceinline__ void mbar_arrive(uint32_t bar) { asm volatile("mbarrier.arrive.shared::cta.b64 _, [%0];" :: "r"(bar) : "memory"); }
__device__ __forceinline__ void mbar_arrive_cluster(uint32_t a) { asm volatile("mbarrier.arrive.shared::cluster.b64 _, [%0];" :: "r"(a) : "memory"); }
__device__ __forceinline__ void mbar_arrive_cluster_rel(uint32_t a) { asm volatile("mbarrier.arrive.release.cluster.shared::cluster.b64 _, [%0];" :: "r"(a) : "memory"); }
__device__ __forceinline__ void arrive2(uint32_t a, uint32_t b, bool on) {
  asm volatile("{\n.reg .pred p;\nsetp.ne.u32 p, %2, 0;\n@p mbarrier.arrive.shared::cta.b64 _, [%0];\n@p mbarrier.arrive.shared::cluster.b64 _, [%1];\n}\n"
               :: "r"(a), "r"(b), "r"((uint32_t)on) : "memory");
}
__device__ __forceinline__ bool mbar_try_wait(uint32_t bar, uint32_t parity) {
  uint32_t ok;
  asm volatile("{\n.reg .pred p;\nmbarrier.try_wait.parity.shared::cta.b64 p, [%1], %2;\nselp.b32 %0, 1, 0, p;\n}\n" : "=r"(ok) : "r"(bar), "r"(parity) : "memory");
  return ok;
}
__device__ __forceinline__ bool mbar_try_wait_cl(uint32_t bar, uint32_t parity) {
  uint32_t ok;
  asm volatile("{\n.reg .pred p;\nmbarrier.try_wait.parity.acquire.cluster.shared::cta.b64 p, [%1], %2;\nselp.b32 %0, 1, 0, p;\n}\n" : "=r"(ok) : "r"(bar), "r"(parity) : "memory");
  return ok;
}
#define TRAP(a, b) __trap()
#define MARK(c)
#define STAMP(i)
#define PSTAMP(h, i)
#define TSTAMP(i)
#define GSTAMP(i)
#define FSTAMP(i)
__device__ __forceinline__ void mbar_wait(uint32_t bar, uint32_t parity) {
  asm volatile("{\n.reg .pred p;\n.reg .u32 c;\nmov.u32 c, 0;\nWL:\nmbarrier.try_wait.parity.shared::cta.b64 p, [%0], %1;\n@p bra WD;\n"
               "add.u32 c, c, 1;\nsetp.lt.u32 p, c, 0x400000;\n@p bra WL;\ntrap;\nWD:\n}\n" :: "r"(bar), "r"(parity) : "memory");
}
__device__ __forceinline__ void mbar_wait_cl(uint32_t bar, uint32_t parity) {
  asm volatile("{\n.reg .pred p;\n.reg .u32 c;\nmov.u32 c, 0;\nWL:\nmbarrier.try_wait.parity.acquire.cluster.shared::cta.b64 p, [%0], %1;\n@p bra WD;\n"
               "add.u32 c, c, 1;\nsetp.lt.u32 p, c, 0x400000;\n@p bra WL;\ntrap;\nWD:\n}\n" :: "r"(bar), "r"(parity) : "memory");
}
__device__ __forceinline__ uint32_t mapa(uint32_t addr, uint32_t rank) { uint32_t r; asm volatile("mapa.shared::cluster.u32 %0, %1, %2;" : "=r"(r) : "r"(addr), "r"(rank)); return r; }
__device__ __forceinline__ void bulk_g2s(uint32_t dst, const void* src, uint32_t bytes, uint32_t bar) {
  asm volatile("cp.async.bulk.shared::cluster.global.mbarrier::complete_tx::bytes [%0], [%1], %2, [%3];" :: "r"(dst), "l"(src), "r"(bytes), "r"(bar) : "memory");
}
__device__ __forceinline__ void bulk_g2s_mc(uint32_t dst, const void* src, uint32_t bytes, uint32_t bar) {
  asm volatile("cp.async.bulk.shared::cluster.global.mbarrier::complete_tx::bytes.multicast::cluster [%0], [%1], %2, [%3], %4;" :: "r"(dst), "l"(src), "r"(bytes), "r"(bar), "h"((uint16_t)3) : "memory");
}
__device__ __forceinline__ void tma3d(uint32_t dst, const CUtensorMap* m, int c1, int c2, uint32_t bar) {
  asm volatile("cp.async.bulk.tensor.3d.shared::cluster.global.mbarrier::complete_tx::bytes [%0], [%1, {%3, %4, %5}], [%2];"
               :: "r"(dst), "l"(m), "r"(bar), "r"(0), "r"(c1), "r"(c2) : "memory");
}
__device__ __forceinline__ void tma3d_mc(uint32_t dst, const CUtensorMap* m, int c1, int c2, uint32_t bar) {
  asm volatile("cp.async.bulk.tensor.3d.shared::cluster.global.mbarrier::complete_tx::bytes.multicast::cluster [%0], [%1, {%3, %4, %5}], [%2], %6;"
               :: "r"(dst), "l"(m), "r"(bar), "r"(0), "r"(c1), "r"(c2), "h"((uint16_t)3) : "memory");
}
__device__ __forceinline__ void tma4d(uint32_t dst, const CUtensorMap* m, int c1, int c2, int c3, uint32_t bar) {
  asm volatile("cp.async.bulk.tensor.4d.shared::cluster.global.mbarrier::complete_tx::bytes [%0], [%1, {%3, %4, %5, %6}], [%2];"
               :: "r"(dst), "l"(m), "r"(bar), "r"(0), "r"(c1), "r"(c2), "r"(c3) : "memory");
}
__device__ __forceinline__ void tma4d_mc(uint32_t dst, const CUtensorMap* m, int c1, int c2, int c3, uint32_t bar) {
  asm volatile("cp.async.bulk.tensor.4d.shared::cluster.global.mbarrier::complete_tx::bytes.multicast::cluster [%0], [%1, {%3, %4, %5, %6}], [%2], %7;"
               :: "r"(dst), "l"(m), "r"(bar), "r"(0), "r"(c1), "r"(c2), "r"(c3), "h"((uint16_t)3) : "memory");
}
__device__ __forceinline__ void tma4d_store(const CUtensorMap* m, uint32_t src, int c1, int c2, int c3) {
  asm volatile("cp.async.bulk.tensor.4d.global.shared::cta.bulk_group [%0, {%2, %3, %4, %5}], [%1];"
               :: "l"(m), "r"(src), "r"(0), "r"(c1), "r"(c2), "r"(c3) : "memory");
}
__device__ __forceinline__ void l2_prefetch(const void* p, uint32_t bytes) { asm volatile("cp.async.bulk.prefetch.L2.global [%0], %1;" :: "l"(p), "r"(bytes) : "memory"); }
__device__ __forceinline__ void map_prefetch(const CUtensorMap* m) { asm volatile("prefetch.tensormap [%0];" :: "l"(m) : "memory"); }
__device__ __forceinline__ bool elect_one() {
  uint32_t p;
  asm volatile("{\n.reg .pred P;\nelect.sync _|P, 0xffffffff;\nselp.b32 %0, 1, 0, P;\n}\n" : "=r"(p));
  return p;
}
__device__ __forceinline__ void wg_fence() { asm volatile("wgmma.fence.sync.aligned;" ::: "memory"); }
__device__ __forceinline__ void wg_commit() { asm volatile("wgmma.commit_group.sync.aligned;" ::: "memory"); }
template <int N> __device__ __forceinline__ void wg_wait() { asm volatile("wgmma.wait_group.sync.aligned %0;" :: "n"(N) : "memory"); }
__device__ __forceinline__ void cluster_arrive() { asm volatile("barrier.cluster.arrive.relaxed.aligned;" ::: "memory"); }
__device__ __forceinline__ void cluster_wait() { asm volatile("barrier.cluster.wait.aligned;" ::: "memory"); }
__device__ __forceinline__ uint32_t cluster_rank() { uint32_t r; asm volatile("mov.u32 %0, %%cluster_ctarank;" : "=r"(r)); return r; }
__device__ __forceinline__ void bar_sync(int id) { asm volatile("bar.sync %0, 256;" :: "r"(id) : "memory"); }
__device__ __forceinline__ void bar_sync_n(int id, int n) { asm volatile("bar.sync %0, %1;" :: "r"(id), "r"(n) : "memory"); }
__device__ __forceinline__ void bar_arrive(int id) { asm volatile("bar.arrive %0, 256;" :: "r"(id) : "memory"); }
__device__ __forceinline__ void fence_async_smem() { asm volatile("fence.proxy.async.shared::cta;" ::: "memory"); }
__device__ __forceinline__ void fence_async_all() { asm volatile("fence.proxy.async;" ::: "memory"); }
__device__ __forceinline__ uint32_t desc_k(uint32_t addr) { return ((addr & 0x3FFFF) >> 4) | (1u << 16); }
__device__ __forceinline__ uint32_t desc_mn(uint32_t addr) { return ((addr & 0x3FFFF) >> 4) | ((CH >> 4) << 16); }
template <int R> __device__ __forceinline__ void reg_alloc() { asm volatile("setmaxnreg.inc.sync.aligned.u32 %0;" :: "n"(R)); }
template <int R> __device__ __forceinline__ void reg_dealloc() { asm volatile("setmaxnreg.dec.sync.aligned.u32 %0;" :: "n"(R)); }
template <int V> struct IC { static constexpr int value = V; };
template <int N> __device__ __forceinline__ void fence_regs(float (&r)[N]) {
#pragma unroll
  for (int i = 0; i < N; i++) asm volatile("" : "+f"(r[i]) :: "memory");
}
template <int N> __device__ __forceinline__ void fence_regs(uint32_t (&r)[N]) {
#pragma unroll
  for (int i = 0; i < N; i++) asm volatile("" : "+r"(r[i]) :: "memory");
}
template <int N> __device__ __forceinline__ void zero_regs(float (&r)[N]) {
#pragma unroll
  for (int i = 0; i < N; i++) r[i] = 0.f;
  fence_regs(r);
}
__device__ __forceinline__ uint32_t pack2(float lo, float hi) { uint32_t r; asm("cvt.rn.bf16x2.f32 %0, %1, %2;" : "=r"(r) : "f"(hi), "f"(lo)); return r; }
__device__ __forceinline__ float blo(uint32_t v) { return __uint_as_float(v << 16); }
__device__ __forceinline__ float bhi(uint32_t v) { return __uint_as_float(v & 0xFFFF0000u); }
__device__ __forceinline__ float ex2(float x) { float r; asm("ex2.approx.ftz.f32 %0, %1;" : "=f"(r) : "f"(x)); return r; }
__device__ __forceinline__ float gelu2(float h) {
  float z = h * fmaf(h * h, 8.f * 0.044715f * 0.7978845608028654f, 2.f * 0.7978845608028654f), t;
  asm("tanh.approx.f32 %0, %1;" : "=f"(t) : "f"(z));
  return fmaf(h, t, h);
}
__device__ __forceinline__ uint32_t hfma2(uint32_t a, uint32_t b, uint32_t c) { uint32_t r; asm("fma.rn.bf16x2 %0, %1, %2, %3;" : "=r"(r) : "r"(a), "r"(b), "r"(c)); return r; }
__device__ __forceinline__ uint32_t hmul2(uint32_t a, uint32_t b) { uint32_t r; asm("mul.rn.bf16x2 %0, %1, %2;" : "=r"(r) : "r"(a), "r"(b)); return r; }
__device__ __forceinline__ void stsm4(uint32_t addr, uint32_t a, uint32_t b, uint32_t c, uint32_t d) {
  asm volatile("stmatrix.sync.aligned.m8n8.x4.shared.b16 [%0], {%1, %2, %3, %4};" :: "r"(addr), "r"(a), "r"(b), "r"(c), "r"(d) : "memory");
}
__device__ __forceinline__ void ldsm4(uint32_t addr, uint32_t& a, uint32_t& b, uint32_t& c, uint32_t& d) {
  asm volatile("ldmatrix.sync.aligned.m8n8.x4.shared.b16 {%0, %1, %2, %3}, [%4];" : "=r"(a), "=r"(b), "=r"(c), "=r"(d) : "r"(addr) : "memory");
}
__device__ __forceinline__ void sts128(uint32_t addr, uint32_t a, uint32_t b, uint32_t c, uint32_t d) {
  asm volatile("st.shared.v4.b32 [%0], {%1, %2, %3, %4};" :: "r"(addr), "r"(a), "r"(b), "r"(c), "r"(d) : "memory");
}
__device__ __forceinline__ void lds128(uint32_t addr, uint32_t (&v)[4]) {
  asm volatile("ld.shared.v4.b32 {%0, %1, %2, %3}, [%4];" : "=r"(v[0]), "=r"(v[1]), "=r"(v[2]), "=r"(v[3]) : "r"(addr) : "memory");
}
__device__ __forceinline__ uint32_t ld_relaxed(const uint32_t* p) { uint32_t v; asm volatile("ld.relaxed.gpu.global.u32 %0, [%1];" : "=r"(v) : "l"(p) : "memory"); return v; }
__device__ __forceinline__ int fresh_tid() { int t; asm volatile("mov.u32 %0, %%tid.x;" : "=r"(t)); return t; }
__device__ __forceinline__ void fence_gpu() { asm volatile("fence.acq_rel.gpu;" ::: "memory"); }
__device__ __forceinline__ void wait_flag(int idx, uint32_t target) {
  uint32_t i = 0;
#pragma unroll 1
  while ((int)(ld_relaxed(&g_flags[idx * 32]) - target) < 0) { __nanosleep(idx == F_WF ? 1000 : 32); if (++i > (1u << 22)) TRAP(idx, target); }
  fence_async_all();
}
__device__ __forceinline__ void signal_flag(int idx) {
  fence_async_all();
  fence_gpu();
  asm volatile("red.relaxed.gpu.global.add.u32 [%0], 1;" :: "l"(&g_flags[idx * 32]) : "memory");
}

__device__ __forceinline__ void wgmma_ss_n256_tb1(float (&d)[128], uint32_t da, uint32_t db, int scale_d) {
  asm volatile("{\n.reg .pred p;\n.reg .b64 da, db;\nsetp.ne.b32 p, %130, 0;\nmov.b64 da, {%128, 0x40000040};\nmov.b64 db, {%129, 0x40000040};\n"
    "wgmma.mma_async.sync.aligned.m64n256k16.f32.bf16.bf16 {%0, %1, %2, %3, %4, %5, %6, %7, %8, %9, %10, %11, %12, %13, %14, %15, %16, %17, %18, %19, %20, %21, %22, %23, %24, %25, %26, %27, %28, %29, %30, %31, %32, %33, %34, %35, %36, %37, %38, %39, %40, %41, %42, %43, %44, %45, %46, %47, %48, %49, %50, %51, %52, %53, %54, %55, %56, %57, %58, %59, %60, %61, %62, %63, %64, %65, %66, %67, %68, %69, %70, %71, %72, %73, %74, %75, %76, %77, %78, %79, %80, %81, %82, %83, %84, %85, %86, %87, %88, %89, %90, %91, %92, %93, %94, %95, %96, %97, %98, %99, %100, %101, %102, %103, %104, %105, %106, %107, %108, %109, %110, %111, %112, %113, %114, %115, %116, %117, %118, %119, %120, %121, %122, %123, %124, %125, %126, %127}, da, db, p, 1, 1, 0, 1;\n}\n"
    : "+f"(d[0]), "+f"(d[1]), "+f"(d[2]), "+f"(d[3]), "+f"(d[4]), "+f"(d[5]), "+f"(d[6]), "+f"(d[7]), "+f"(d[8]), "+f"(d[9]), "+f"(d[10]), "+f"(d[11]), "+f"(d[12]), "+f"(d[13]), "+f"(d[14]), "+f"(d[15]), "+f"(d[16]), "+f"(d[17]), "+f"(d[18]), "+f"(d[19]), "+f"(d[20]), "+f"(d[21]), "+f"(d[22]), "+f"(d[23]), "+f"(d[24]), "+f"(d[25]), "+f"(d[26]), "+f"(d[27]), "+f"(d[28]), "+f"(d[29]), "+f"(d[30]), "+f"(d[31]), "+f"(d[32]), "+f"(d[33]), "+f"(d[34]), "+f"(d[35]), "+f"(d[36]), "+f"(d[37]), "+f"(d[38]), "+f"(d[39]), "+f"(d[40]), "+f"(d[41]), "+f"(d[42]), "+f"(d[43]), "+f"(d[44]), "+f"(d[45]), "+f"(d[46]), "+f"(d[47]), "+f"(d[48]), "+f"(d[49]), "+f"(d[50]), "+f"(d[51]), "+f"(d[52]), "+f"(d[53]), "+f"(d[54]), "+f"(d[55]), "+f"(d[56]), "+f"(d[57]), "+f"(d[58]), "+f"(d[59]), "+f"(d[60]), "+f"(d[61]), "+f"(d[62]), "+f"(d[63]), "+f"(d[64]), "+f"(d[65]), "+f"(d[66]), "+f"(d[67]), "+f"(d[68]), "+f"(d[69]), "+f"(d[70]), "+f"(d[71]), "+f"(d[72]), "+f"(d[73]), "+f"(d[74]), "+f"(d[75]), "+f"(d[76]), "+f"(d[77]), "+f"(d[78]), "+f"(d[79]), "+f"(d[80]), "+f"(d[81]), "+f"(d[82]), "+f"(d[83]), "+f"(d[84]), "+f"(d[85]), "+f"(d[86]), "+f"(d[87]), "+f"(d[88]), "+f"(d[89]), "+f"(d[90]), "+f"(d[91]), "+f"(d[92]), "+f"(d[93]), "+f"(d[94]), "+f"(d[95]), "+f"(d[96]), "+f"(d[97]), "+f"(d[98]), "+f"(d[99]), "+f"(d[100]), "+f"(d[101]), "+f"(d[102]), "+f"(d[103]), "+f"(d[104]), "+f"(d[105]), "+f"(d[106]), "+f"(d[107]), "+f"(d[108]), "+f"(d[109]), "+f"(d[110]), "+f"(d[111]), "+f"(d[112]), "+f"(d[113]), "+f"(d[114]), "+f"(d[115]), "+f"(d[116]), "+f"(d[117]), "+f"(d[118]), "+f"(d[119]), "+f"(d[120]), "+f"(d[121]), "+f"(d[122]), "+f"(d[123]), "+f"(d[124]), "+f"(d[125]), "+f"(d[126]), "+f"(d[127])
    : "r"(da), "r"(db), "r"(scale_d));
}

__device__ __forceinline__ void wgmma_ss_n256_tb0(float (&d)[128], uint32_t da, uint32_t db, int scale_d) {
  asm volatile("{\n.reg .pred p;\n.reg .b64 da, db;\nsetp.ne.b32 p, %130, 0;\nmov.b64 da, {%128, 0x40000040};\nmov.b64 db, {%129, 0x40000040};\n"
    "wgmma.mma_async.sync.aligned.m64n256k16.f32.bf16.bf16 {%0, %1, %2, %3, %4, %5, %6, %7, %8, %9, %10, %11, %12, %13, %14, %15, %16, %17, %18, %19, %20, %21, %22, %23, %24, %25, %26, %27, %28, %29, %30, %31, %32, %33, %34, %35, %36, %37, %38, %39, %40, %41, %42, %43, %44, %45, %46, %47, %48, %49, %50, %51, %52, %53, %54, %55, %56, %57, %58, %59, %60, %61, %62, %63, %64, %65, %66, %67, %68, %69, %70, %71, %72, %73, %74, %75, %76, %77, %78, %79, %80, %81, %82, %83, %84, %85, %86, %87, %88, %89, %90, %91, %92, %93, %94, %95, %96, %97, %98, %99, %100, %101, %102, %103, %104, %105, %106, %107, %108, %109, %110, %111, %112, %113, %114, %115, %116, %117, %118, %119, %120, %121, %122, %123, %124, %125, %126, %127}, da, db, p, 1, 1, 0, 0;\n}\n"
    : "+f"(d[0]), "+f"(d[1]), "+f"(d[2]), "+f"(d[3]), "+f"(d[4]), "+f"(d[5]), "+f"(d[6]), "+f"(d[7]), "+f"(d[8]), "+f"(d[9]), "+f"(d[10]), "+f"(d[11]), "+f"(d[12]), "+f"(d[13]), "+f"(d[14]), "+f"(d[15]), "+f"(d[16]), "+f"(d[17]), "+f"(d[18]), "+f"(d[19]), "+f"(d[20]), "+f"(d[21]), "+f"(d[22]), "+f"(d[23]), "+f"(d[24]), "+f"(d[25]), "+f"(d[26]), "+f"(d[27]), "+f"(d[28]), "+f"(d[29]), "+f"(d[30]), "+f"(d[31]), "+f"(d[32]), "+f"(d[33]), "+f"(d[34]), "+f"(d[35]), "+f"(d[36]), "+f"(d[37]), "+f"(d[38]), "+f"(d[39]), "+f"(d[40]), "+f"(d[41]), "+f"(d[42]), "+f"(d[43]), "+f"(d[44]), "+f"(d[45]), "+f"(d[46]), "+f"(d[47]), "+f"(d[48]), "+f"(d[49]), "+f"(d[50]), "+f"(d[51]), "+f"(d[52]), "+f"(d[53]), "+f"(d[54]), "+f"(d[55]), "+f"(d[56]), "+f"(d[57]), "+f"(d[58]), "+f"(d[59]), "+f"(d[60]), "+f"(d[61]), "+f"(d[62]), "+f"(d[63]), "+f"(d[64]), "+f"(d[65]), "+f"(d[66]), "+f"(d[67]), "+f"(d[68]), "+f"(d[69]), "+f"(d[70]), "+f"(d[71]), "+f"(d[72]), "+f"(d[73]), "+f"(d[74]), "+f"(d[75]), "+f"(d[76]), "+f"(d[77]), "+f"(d[78]), "+f"(d[79]), "+f"(d[80]), "+f"(d[81]), "+f"(d[82]), "+f"(d[83]), "+f"(d[84]), "+f"(d[85]), "+f"(d[86]), "+f"(d[87]), "+f"(d[88]), "+f"(d[89]), "+f"(d[90]), "+f"(d[91]), "+f"(d[92]), "+f"(d[93]), "+f"(d[94]), "+f"(d[95]), "+f"(d[96]), "+f"(d[97]), "+f"(d[98]), "+f"(d[99]), "+f"(d[100]), "+f"(d[101]), "+f"(d[102]), "+f"(d[103]), "+f"(d[104]), "+f"(d[105]), "+f"(d[106]), "+f"(d[107]), "+f"(d[108]), "+f"(d[109]), "+f"(d[110]), "+f"(d[111]), "+f"(d[112]), "+f"(d[113]), "+f"(d[114]), "+f"(d[115]), "+f"(d[116]), "+f"(d[117]), "+f"(d[118]), "+f"(d[119]), "+f"(d[120]), "+f"(d[121]), "+f"(d[122]), "+f"(d[123]), "+f"(d[124]), "+f"(d[125]), "+f"(d[126]), "+f"(d[127])
    : "r"(da), "r"(db), "r"(scale_d));
}

__device__ __forceinline__ void wgmma_rs_n256_tb1(float (&d)[128], uint32_t a0, uint32_t a1, uint32_t a2, uint32_t a3, uint32_t db, int scale_d) {
  asm volatile("{\n.reg .pred p;\n.reg .b64 db;\nsetp.ne.b32 p, %133, 0;\nmov.b64 db, {%132, 0x40000040};\n"
    "wgmma.mma_async.sync.aligned.m64n256k16.f32.bf16.bf16 {%0, %1, %2, %3, %4, %5, %6, %7, %8, %9, %10, %11, %12, %13, %14, %15, %16, %17, %18, %19, %20, %21, %22, %23, %24, %25, %26, %27, %28, %29, %30, %31, %32, %33, %34, %35, %36, %37, %38, %39, %40, %41, %42, %43, %44, %45, %46, %47, %48, %49, %50, %51, %52, %53, %54, %55, %56, %57, %58, %59, %60, %61, %62, %63, %64, %65, %66, %67, %68, %69, %70, %71, %72, %73, %74, %75, %76, %77, %78, %79, %80, %81, %82, %83, %84, %85, %86, %87, %88, %89, %90, %91, %92, %93, %94, %95, %96, %97, %98, %99, %100, %101, %102, %103, %104, %105, %106, %107, %108, %109, %110, %111, %112, %113, %114, %115, %116, %117, %118, %119, %120, %121, %122, %123, %124, %125, %126, %127}, {%128, %129, %130, %131}, db, p, 1, 1, 1;\n}\n"
    : "+f"(d[0]), "+f"(d[1]), "+f"(d[2]), "+f"(d[3]), "+f"(d[4]), "+f"(d[5]), "+f"(d[6]), "+f"(d[7]), "+f"(d[8]), "+f"(d[9]), "+f"(d[10]), "+f"(d[11]), "+f"(d[12]), "+f"(d[13]), "+f"(d[14]), "+f"(d[15]), "+f"(d[16]), "+f"(d[17]), "+f"(d[18]), "+f"(d[19]), "+f"(d[20]), "+f"(d[21]), "+f"(d[22]), "+f"(d[23]), "+f"(d[24]), "+f"(d[25]), "+f"(d[26]), "+f"(d[27]), "+f"(d[28]), "+f"(d[29]), "+f"(d[30]), "+f"(d[31]), "+f"(d[32]), "+f"(d[33]), "+f"(d[34]), "+f"(d[35]), "+f"(d[36]), "+f"(d[37]), "+f"(d[38]), "+f"(d[39]), "+f"(d[40]), "+f"(d[41]), "+f"(d[42]), "+f"(d[43]), "+f"(d[44]), "+f"(d[45]), "+f"(d[46]), "+f"(d[47]), "+f"(d[48]), "+f"(d[49]), "+f"(d[50]), "+f"(d[51]), "+f"(d[52]), "+f"(d[53]), "+f"(d[54]), "+f"(d[55]), "+f"(d[56]), "+f"(d[57]), "+f"(d[58]), "+f"(d[59]), "+f"(d[60]), "+f"(d[61]), "+f"(d[62]), "+f"(d[63]), "+f"(d[64]), "+f"(d[65]), "+f"(d[66]), "+f"(d[67]), "+f"(d[68]), "+f"(d[69]), "+f"(d[70]), "+f"(d[71]), "+f"(d[72]), "+f"(d[73]), "+f"(d[74]), "+f"(d[75]), "+f"(d[76]), "+f"(d[77]), "+f"(d[78]), "+f"(d[79]), "+f"(d[80]), "+f"(d[81]), "+f"(d[82]), "+f"(d[83]), "+f"(d[84]), "+f"(d[85]), "+f"(d[86]), "+f"(d[87]), "+f"(d[88]), "+f"(d[89]), "+f"(d[90]), "+f"(d[91]), "+f"(d[92]), "+f"(d[93]), "+f"(d[94]), "+f"(d[95]), "+f"(d[96]), "+f"(d[97]), "+f"(d[98]), "+f"(d[99]), "+f"(d[100]), "+f"(d[101]), "+f"(d[102]), "+f"(d[103]), "+f"(d[104]), "+f"(d[105]), "+f"(d[106]), "+f"(d[107]), "+f"(d[108]), "+f"(d[109]), "+f"(d[110]), "+f"(d[111]), "+f"(d[112]), "+f"(d[113]), "+f"(d[114]), "+f"(d[115]), "+f"(d[116]), "+f"(d[117]), "+f"(d[118]), "+f"(d[119]), "+f"(d[120]), "+f"(d[121]), "+f"(d[122]), "+f"(d[123]), "+f"(d[124]), "+f"(d[125]), "+f"(d[126]), "+f"(d[127])
    : "r"(a0), "r"(a1), "r"(a2), "r"(a3), "r"(db), "r"(scale_d));
}

__device__ __forceinline__ void wgmma_ss_n64_tb0(float (&d)[32], uint32_t da, uint32_t db, int scale_d) {
  asm volatile("{\n.reg .pred p;\n.reg .b64 da, db;\nsetp.ne.b32 p, %34, 0;\nmov.b64 da, {%32, 0x40000040};\nmov.b64 db, {%33, 0x40000040};\n"
    "wgmma.mma_async.sync.aligned.m64n64k16.f32.bf16.bf16 {%0, %1, %2, %3, %4, %5, %6, %7, %8, %9, %10, %11, %12, %13, %14, %15, %16, %17, %18, %19, %20, %21, %22, %23, %24, %25, %26, %27, %28, %29, %30, %31}, da, db, p, 1, 1, 0, 0;\n}\n"
    : "+f"(d[0]), "+f"(d[1]), "+f"(d[2]), "+f"(d[3]), "+f"(d[4]), "+f"(d[5]), "+f"(d[6]), "+f"(d[7]), "+f"(d[8]), "+f"(d[9]), "+f"(d[10]), "+f"(d[11]), "+f"(d[12]), "+f"(d[13]), "+f"(d[14]), "+f"(d[15]), "+f"(d[16]), "+f"(d[17]), "+f"(d[18]), "+f"(d[19]), "+f"(d[20]), "+f"(d[21]), "+f"(d[22]), "+f"(d[23]), "+f"(d[24]), "+f"(d[25]), "+f"(d[26]), "+f"(d[27]), "+f"(d[28]), "+f"(d[29]), "+f"(d[30]), "+f"(d[31])
    : "r"(da), "r"(db), "r"(scale_d));
}

__device__ __forceinline__ void wgmma_rs_n64_tb0(float (&d)[32], uint32_t a0, uint32_t a1, uint32_t a2, uint32_t a3, uint32_t db, int scale_d) {
  asm volatile("{\n.reg .pred p;\n.reg .b64 db;\nsetp.ne.b32 p, %37, 0;\nmov.b64 db, {%36, 0x40000040};\n"
    "wgmma.mma_async.sync.aligned.m64n64k16.f32.bf16.bf16 {%0, %1, %2, %3, %4, %5, %6, %7, %8, %9, %10, %11, %12, %13, %14, %15, %16, %17, %18, %19, %20, %21, %22, %23, %24, %25, %26, %27, %28, %29, %30, %31}, {%32, %33, %34, %35}, db, p, 1, 1, 0;\n}\n"
    : "+f"(d[0]), "+f"(d[1]), "+f"(d[2]), "+f"(d[3]), "+f"(d[4]), "+f"(d[5]), "+f"(d[6]), "+f"(d[7]), "+f"(d[8]), "+f"(d[9]), "+f"(d[10]), "+f"(d[11]), "+f"(d[12]), "+f"(d[13]), "+f"(d[14]), "+f"(d[15]), "+f"(d[16]), "+f"(d[17]), "+f"(d[18]), "+f"(d[19]), "+f"(d[20]), "+f"(d[21]), "+f"(d[22]), "+f"(d[23]), "+f"(d[24]), "+f"(d[25]), "+f"(d[26]), "+f"(d[27]), "+f"(d[28]), "+f"(d[29]), "+f"(d[30]), "+f"(d[31])
    : "r"(a0), "r"(a1), "r"(a2), "r"(a3), "r"(db), "r"(scale_d));
}

template <int O>
__device__ __forceinline__ void wgmma_ss_n128_tb1(float (&d)[128], uint32_t da, uint32_t db, int scale_d) {
  asm volatile("{\n.reg .pred p;\n.reg .b64 da, db;\nsetp.ne.b32 p, %66, 0;\nmov.b64 da, {%64, 0x40000040};\nmov.b64 db, {%65, 0x40000040};\n"
    "wgmma.mma_async.sync.aligned.m64n128k16.f32.bf16.bf16 {%0, %1, %2, %3, %4, %5, %6, %7, %8, %9, %10, %11, %12, %13, %14, %15, %16, %17, %18, %19, %20, %21, %22, %23, %24, %25, %26, %27, %28, %29, %30, %31, %32, %33, %34, %35, %36, %37, %38, %39, %40, %41, %42, %43, %44, %45, %46, %47, %48, %49, %50, %51, %52, %53, %54, %55, %56, %57, %58, %59, %60, %61, %62, %63}, da, db, p, 1, 1, 0, 1;\n}\n"
    : "+f"(d[O + 0]), "+f"(d[O + 1]), "+f"(d[O + 2]), "+f"(d[O + 3]), "+f"(d[O + 4]), "+f"(d[O + 5]), "+f"(d[O + 6]), "+f"(d[O + 7]), "+f"(d[O + 8]), "+f"(d[O + 9]), "+f"(d[O + 10]), "+f"(d[O + 11]), "+f"(d[O + 12]), "+f"(d[O + 13]), "+f"(d[O + 14]), "+f"(d[O + 15]), "+f"(d[O + 16]), "+f"(d[O + 17]), "+f"(d[O + 18]), "+f"(d[O + 19]), "+f"(d[O + 20]), "+f"(d[O + 21]), "+f"(d[O + 22]), "+f"(d[O + 23]), "+f"(d[O + 24]), "+f"(d[O + 25]), "+f"(d[O + 26]), "+f"(d[O + 27]), "+f"(d[O + 28]), "+f"(d[O + 29]), "+f"(d[O + 30]), "+f"(d[O + 31]), "+f"(d[O + 32]), "+f"(d[O + 33]), "+f"(d[O + 34]), "+f"(d[O + 35]), "+f"(d[O + 36]), "+f"(d[O + 37]), "+f"(d[O + 38]), "+f"(d[O + 39]), "+f"(d[O + 40]), "+f"(d[O + 41]), "+f"(d[O + 42]), "+f"(d[O + 43]), "+f"(d[O + 44]), "+f"(d[O + 45]), "+f"(d[O + 46]), "+f"(d[O + 47]), "+f"(d[O + 48]), "+f"(d[O + 49]), "+f"(d[O + 50]), "+f"(d[O + 51]), "+f"(d[O + 52]), "+f"(d[O + 53]), "+f"(d[O + 54]), "+f"(d[O + 55]), "+f"(d[O + 56]), "+f"(d[O + 57]), "+f"(d[O + 58]), "+f"(d[O + 59]), "+f"(d[O + 60]), "+f"(d[O + 61]), "+f"(d[O + 62]), "+f"(d[O + 63])
    : "r"(da), "r"(db), "r"(scale_d));
}

struct Ctx {
  uint32_t sb;
  uint32_t pdelta;
  uint32_t fb, ph;
  bool l0;
  __device__ __forceinline__ uint32_t slot(uint32_t n) const { return sb + (n % NS) * SLOT; }
  __device__ __forceinline__ uint32_t full(uint32_t n, uint32_t w) const { return sb + OFF_BAR + 40 * w + 8 * (n % NS); }
  __device__ __forceinline__ uint32_t empty(uint32_t n) const { return sb + OFF_BAR + 80 + 8 * (n % NS); }
  __device__ __forceinline__ uint32_t afull(int h) const { return sb + OFF_BAR + 120 + 8 * h; }
  __device__ __forceinline__ uint32_t afree(int h) const { return sb + OFF_BAR + 136 + 8 * h; }
  __device__ __forceinline__ uint32_t gbar() const { return sb + OFF_BAR + 152; }
  __device__ __forceinline__ uint32_t dbar() const { return sb + OFF_BAR + 160; }
  __device__ __forceinline__ uint32_t xbar() const { return sb + OFF_BAR + 168; }
  __device__ __forceinline__ uint32_t sbar(int w) const { return sb + OFF_BAR + 176 + 8 * w; }
  __device__ __forceinline__ void wait_full(uint32_t n) {
    const uint32_t s = n % NS;
    mbar_wait(fb + 8 * s, (ph >> s) & 1);
    ph ^= 1u << s;
  }
  __device__ __forceinline__ uint32_t cbar() const { return sb + OFF_BAR + 192; }
  __device__ __forceinline__ uint32_t fbar(int i) const { return sb + OFF_BAR + 200 + 8 * i; }
  template <int LO> __device__ __forceinline__ uint32_t rdelta(uint32_t n) const { return n - LO < N_FIN0 - N_ATT0 || (n < N_ATT0 ? (MCM >> ((n + NS) & 7) & 1) : MCF) ? pdelta : 0; }
  template <int LO = N_ATT0 - NS> __device__ __forceinline__ void release(uint32_t n) const { const uint32_t e = empty(n); arrive2(e, e + rdelta<LO>(n), l0); }
};

template <int TB, int LO, class Pre, class Post>
__device__ __forceinline__ void gemm8(Ctx& cx, float (&acc)[128], uint32_t n0, Pre pre, Post post) {
  zero_regs(acc);
  uint32_t s = n0 % NS, e = 0, e2 = 0;
  uint32_t fb = cx.fb + 8 * s, par = (cx.ph >> s) & 1;
  uint32_t da = desc_k(cx.sb + OFF_Q), db = TB ? desc_mn(cx.sb + s * SLOT) : desc_k(cx.sb + s * SLOT);
#pragma unroll 1
  for (int kb = 0; kb < 8; kb++) {
    pre(kb);
    if (n0 < 48) STAMP(240 + n0 + kb);
    mbar_wait(fb, par);
    wg_fence();
#pragma unroll
    for (int k = 0; k < 4; k++) {
      if (TB) wgmma_ss_n256_tb1(acc, da + k * 2, db + k * 128, 1);
      else wgmma_ss_n256_tb0(acc, da + k * 2, db + k * 2, 1);
    }
    wg_commit();
    const uint32_t pe = e, pe2 = e2;
    e = cx.sb + OFF_BAR + 80 + 8 * s;
    e2 = e + cx.rdelta<LO>(n0 + kb);
    cx.ph ^= 1u << s;
    db += s == NS - 1 ? -(NS - 1) * (SLOT >> 4) : (SLOT >> 4);
    s = s == NS - 1 ? 0 : s + 1;
    fb = cx.fb + 8 * s; par = (cx.ph >> s) & 1;
    da += CH >> 4;
    wg_wait<1>();
    arrive2(pe, pe2, kb > 0 && cx.l0);
    if (kb > 0) post(kb - 1);
  }
  wg_wait<0>();
  fence_regs(acc);
  arrive2(e, e2, cx.l0);
  post(7);
}

__device__ __forceinline__ int sigma(int r) { return (r & ~30) | ((r & 6) << 2) | ((r & 24) >> 2); }

__global__ void __cluster_dims__(2, 1, 1) __launch_bounds__(384, 1)
bf_kernel(const __grid_constant__ Maps maps, const __grid_constant__ Ptrs wp, const __nv_bfloat16* __restrict__ x,
          const __nv_bfloat16* __restrict__ dw, __nv_bfloat16* __restrict__ out, int mode) {
  extern __shared__ __align__(1024) uint8_t smem_raw[];
  if (threadIdx.x < 256) { GSTAMP(502); STAMP(503); }
  Ctx cx;
  cx.sb = smem_u32(smem_raw);
  const uint32_t sb = cx.sb;
  const int tid = threadIdx.x, lane = tid & 31, warp = __shfl_sync(~0u, tid >> 5, 0);
  const uint32_t rank = cluster_rank();
  cx.pdelta = mapa(sb, rank ^ 1) - sb;
  const int cid = blockIdx.x >> 1;
  const bool spare = cid < 2;
  const int pairi = cid - 2, batch = pairi >> 5, pp = pairi & 31;
  const int row0 = 125 * pp - 1 + 64 * (int)rank;
  if (tid == 0) {
    mbar_init(cx.xbar(), 1);
    asm volatile("fence.mbarrier_init.release.cluster;" ::: "memory");
    if (!spare) {
      mbar_expect_tx(cx.xbar(), TILE);
      tma4d(sb + OFF_Q, &maps.x, row0, 0, batch, cx.xbar());
      tma4d(sb + OFF_Q + SLOT, &maps.x, row0, 4, batch, cx.xbar());
    }
    if (sb & 1023) TRAP(sb, 12345);
    TSTAMP(490);
  } else if (tid == 32) {
#pragma unroll 1
    for (int i = 0; i < (int)NS; i++) { mbar_init(cx.full(i, 0), 1); mbar_init(cx.full(i, 1), 1); mbar_init(cx.empty(i), 8); }
    mbar_init(cx.afull(0), 1); mbar_init(cx.afull(1), 1);
    mbar_init(cx.afree(0), spare ? 4 : 8); mbar_init(cx.afree(1), 4);
    mbar_init(cx.gbar(), 2); mbar_init(cx.dbar(), 8); mbar_init(cx.cbar(), 2);
    mbar_init(cx.sbar(0), spare ? 4 : 8); mbar_init(cx.sbar(1), spare ? 4 : 8);
#pragma unroll 1
    for (int i = 0; i < 6; i++) mbar_init(cx.fbar(i), 1);
    TSTAMP(491);
    asm volatile("fence.mbarrier_init.release.cluster;" ::: "memory");
    TSTAMP(492);
  } else if (tid == 64) {
    if (!spare && mode != 2) {
      const int i = blockIdx.x - 4;
      l2_prefetch((i & 1 ? wp.wq : wp.wk) + (i >> 1) * 8192, 8192);
    }
    if (!spare && mode != 1) l2_prefetch(wp.wup + (blockIdx.x - 4) * 8192, 8192);
    TSTAMP(493);
    map_prefetch(spare ? &maps.k : &maps.up);
    map_prefetch(spare ? &maps.q : &maps.xs);
    map_prefetch(&maps.xl);
    TSTAMP(494);
  }
  if (threadIdx.x < 256) STAMP(504);
  __syncthreads();
  if (tid == 96) TSTAMP(495);
  cluster_arrive();
  if (threadIdx.x < 256) STAMP(505);

  if (__builtin_expect(warp >= 8, 1)) {
    reg_dealloc<PREG>();
    cluster_wait();
    const uint32_t ro = rank * 16384;
    if (warp == 8) {
      uint32_t si = 0, par = 1, pn = 0;
      auto step = [&](uint32_t w, auto issue) {
        mbar_wait(sb + OFF_BAR + 80 + 8 * si, par);
        const uint32_t fb = sb + OFF_BAR + 40 * w + 8 * si, s = sb + si * SLOT;
        if (elect_one()) { PSTAMP(0, pn); mbar_expect_tx(fb, SLOT); issue(s, fb); PSTAMP(1, pn); }
        pn++;
        if (++si == NS) { si = 0; par ^= 1; }
      };
      if (spare) {
        if (mode != 2) {
#pragma unroll 1
          for (uint32_t n = 0; n < 128; n++) {
            const uint32_t w = (n >> 3) & 1, kb = n & 7, j = n >> 4;
            const CUtensorMap* m = j < 2 ? &maps.k : ((j == 2 || j == 4) ? &maps.ao : &maps.mg);
            const int c1 = j < 2 ? 256 * w + 128 * rank : 64 * kb + (j >= 6 ? 512 : 0), c2 = j < 2 ? kb : 4 * w + 2 * rank;
            step(w, [&](uint32_t s, uint32_t fb) { tma3d_mc(s + ro, m, c1, c2, fb); });
          }
        }
      } else if (mode != 1) {
#pragma unroll 1
        for (uint32_t n = 0; n < 32; n++) {
          const uint32_t w = (n >> 3) & 1;
          step(w, [&](uint32_t s, uint32_t fb) {
            const int c2 = (n < 16 ? 8 : 0) + 4 * w;
            if (n >= NS && (MCM >> (n & 7) & 1)) tma3d_mc(s + ro, &maps.up, 64 * (n & 7), c2 + 2 * rank, fb);
            else { tma3d(s, &maps.up, 64 * (n & 7), c2, fb); tma3d(s + 16384, &maps.up, 64 * (n & 7), c2 + 2, fb); }
          });
        }
#pragma unroll 1
        for (uint32_t n = 0; n < 16; n++) {
          const uint32_t w = n >> 3, kb = n & 7;
          if ((n & 3) == 0) mbar_wait(cx.fbar(n >> 2), 0);
          step(w, [&](uint32_t s, uint32_t fb) {
            const uint8_t* src = g_wqk + kb * TILE + w * SLOT;
            if (MCM >> (n & 7) & 1) bulk_g2s_mc(s + ro, src + ro, 16384, fb); else bulk_g2s(s, src, SLOT, fb);
          });
        }
        mbar_wait(cx.fbar(4), 0);
#pragma unroll 1
        for (uint32_t i = 0; i < 2 * NTILE; i++) {
          const uint32_t t = i >> 1;
          step(t & 1, [&](uint32_t s, uint32_t fb) { tma4d_mc(s + ro, &maps.xl, 64 * t, 4 * ((t ^ i) & 1) + 2 * rank, batch, fb); });
        }
        mbar_wait(cx.fbar(5), 0);
#pragma unroll 1
        for (uint32_t n = 0; n < 32; n++) {
          const uint32_t i = n >> 1, w = n & 1;
          step(w, [&](uint32_t s, uint32_t fb) {
            const uint8_t* src = g_wf + (i < 8 ? i : 8 + ((i + 4 * w) & 7)) * TILE + w * SLOT;
            if (i >= 12) {
              src = g_wf + (12 - 4 * w + 2 * (i & 1)) * TILE + w * SLOT + (i & 2) * 8192;
              bulk_g2s(s, src, 16384, fb); bulk_g2s(s + 16384, src + TILE, 16384, fb);
            } else bulk_g2s(s, src, SLOT, fb);
          });
        }
      }
    } else if (warp == 10) {
      if (lane == 0) {
        if (!spare && mode != 1) {
          const uint32_t ep1 = ld_relaxed(&g_flags[F_DONE * 32]) / NCTA + 1;
#pragma unroll 1
          for (int i = 0; i < 6; i++) {
            wait_flag(i < 4 ? F_WQK + 2 * (i & 1) + (i >> 1) : (i == 4 ? F_XA + batch : F_WF), ep1 * (i < 4 ? 4 : (i == 4 ? 64 : 32)));
            mbar_arrive(cx.fbar(i));
          }
        }
        mbar_wait(cx.dbar(), 0);
      }
    } else if (spare) {
      if (lane == 0 && mode != 2) {
        if (warp == 9) {
          const int s = 2 * cid + rank;
#pragma unroll 1
          for (int rh = 0; rh < 12; rh++) {
            const int r = rh >> 1, h = rh & 1;
            const CUtensorMap* m = r < 2 ? &maps.q : (r < 4 ? &maps.v : &maps.dn);
            const int row = 64 * (s + 4 * (r & 1));
            if (r > 0) mbar_wait(cx.afree(h), (r - 1) & 1);
            mbar_expect_tx(cx.afull(h), SLOT);
            tma3d(sb + OFF_Q + h * SLOT, m, row, 4 * h, cx.afull(h));
            tma3d(sb + OFF_Q + h * SLOT + 16384, m, row, 4 * h + 2, cx.afull(h));
          }
        } else {
#pragma unroll 1
          for (int e = 0; e < 12; e++) {
            mbar_wait(cx.sbar(e & 1), (e >> 1) & 1);
            signal_flag(e < 4 ? F_WQK + e : F_WF);
          }
        }
      }
    } else {
      if (warp == 11) {
        bar_sync_n(3, 288);
        if (lane == 0 && mode != 2) {
#pragma unroll 1
          for (int i = 0; i < 8; i++) {
            tma4d_store(&maps.xs, sb + OFF_Q + i * CH, row0 + 1, i, batch);
            asm volatile("cp.async.bulk.commit_group;" ::: "memory");
            __nanosleep(XPACE);
          }
          const int i = blockIdx.x - 4;
          l2_prefetch(wp.wv + i * 4096, 4096); l2_prefetch(wp.wao + i * 4096, 4096);
          l2_prefetch(wp.wmg + i * 8192, 8192); l2_prefetch(wp.wdn + i * 4096, 4096);
          asm volatile("cp.async.bulk.wait_group 0;" ::: "memory");
          signal_flag(F_XA + batch);
        }
        if (lane == 0 && mode != 1) {
          mbar_wait(cx.sbar(0), 0);
          fence_gpu();
          mbar_arrive(cx.gbar());
          mbar_arrive_cluster(cx.gbar() + cx.pdelta);
        }
        __syncwarp();
      }
      if (mode != 1) {
        const int ch = 4 * (warp >> 1 & 1) + (lane >> 3), lu = lane & 7;
        uint32_t dk[3][4];
#pragma unroll
        for (int k = 0; k < 3; k++)
#pragma unroll
          for (int jj = 0; jj < 4; jj++) dk[k][jj] = __ldg((const uint32_t*)dw + 256 * k + 32 * ch + 16 * (lu >> 2) + 4 * jj + (lu & 3));
        mbar_wait_cl(cx.gbar(), 0);
        mbar_wait(cx.sbar(1), 0);
        uint8_t* up_ = g_uc + (size_t)(2 * pairi) * TILE + ch * CH;
        const float4* sp_ = (const float4*)g_st + pairi * 128;
        uint32_t p1[4] = {0, 0, 0, 0}, p2[4] = {0, 0, 0, 0};
        uint32_t oo = 0;
#pragma unroll 1
        for (int L = 64 * (int)rank - 1; L <= 64 * (int)rank + (NOCONV ? -2 : 64); L++) {
          const uint32_t Lc = min(max(L, 0), 127), oc = (Lc >> 6) * TILE + (Lc & 63) * 128 + ((lu ^ (Lc & 7)) << 4);
          const uint4 g = __ldcg((const uint4*)(up_ + 128 * TILE + oc));
          const float4 st = __ldcg(sp_ + Lc);
          uint4* uo = (uint4*)(up_ + oo);
          const uint4 u = __ldcg(uo);
          oo = oc;
          const float mu_ = (st.x + st.z) * (1.f / DD);
          const float r = rsqrtf(fmaxf(fmaf(-mu_, mu_, (st.y + st.w) * (1.f / DD)), 0.f) + 1e-5f), m = -mu_ * r;
          const uint32_t gg[4] = {g.x, g.y, g.z, g.w}, uu[4] = {u.x, u.y, u.z, u.w};
          uint32_t o[4];
#pragma unroll
          for (int jj = 0; jj < 4; jj++) {
            const uint32_t gn = pack2(fmaf(blo(gg[jj]), r, m), fmaf(bhi(gg[jj]), r, m));
            o[jj] = hmul2(uu[jj], hfma2(gn, dk[2][jj], p1[jj]));
            p1[jj] = hfma2(gn, dk[1][jj], p2[jj]);
            p2[jj] = hmul2(gn, dk[0][jj]);
          }
          if (L > 64 * (int)rank) __stcg(uo, make_uint4(o[0], o[1], o[2], o[3]));
        }
        __syncwarp();
        if (lane == 0) mbar_arrive(cx.cbar());
        if (lane == 0 && warp == 9) {
          const uint8_t* uc = g_uc + (size_t)(2 * pairi + rank) * TILE;
          mbar_wait(cx.cbar(), 0);
#pragma unroll 1
          for (int h = 0; h < 2; h++) {
            mbar_wait(cx.afree(h), 0);
            if (h == 0) {
              const int r0 = max(row0, 0), r1 = min(row0 + 64, TT);
              l2_prefetch(x + ((size_t)batch * TT + r0) * DD, (r1 - r0) * DD * 2);
            }
            fence_async_all();
            mbar_expect_tx(cx.afull(h), h ? CH : 7 * CH);
            bulk_g2s(sb + OFF_Q + h * 7 * CH, uc + h * 7 * CH, h ? CH : 7 * CH, cx.afull(h));
          }
        }
      }
    }
    __syncwarp();
    cluster_arrive();
    cluster_wait();
  } else {
    reg_alloc<CREG>();
    STAMP(0); GSTAMP(500);
    const int w = warp >> 2, wq = warp & 3, q = lane >> 2, c = lane & 3;
    cx.fb = cx.full(0, w); cx.ph = 0; cx.l0 = lane == 0;
    const int rlo = 16 * wq + q;
    const int mrow = 16 * wq + (lane & 15);
    const uint32_t moff = mrow * 128, mx = mrow & 7, mu = lane >> 4;
    float acc[128];

    if (spare) {
      cluster_wait();
      if (mode != 2) {
        const int s = 2 * cid + rank;
        int ar = 0;
#pragma unroll 1
        for (int j = 0; j < 8; j++) {
          MARK(mode * 1000 + j * 10); STAMP(1 + 2 * j);
          const bool tmaA = (j != 3 && j != 5), t1 = (j == 2 || j == 4), nextTma = (j != 2 && j != 4 && j != 7);
          auto pre = [&](int kb) {
            if (tmaA && (kb & 3) == 0) mbar_wait(cx.afull(kb >> 2), ar & 1);
            if (!tmaA && kb == (w ? 0 : 4)) bar_sync(w ? 5 : 6);
          };
          auto post = [&](int kb) {
            if (w == 1 && (kb & 3) == 3) {
              if (nextTma) { if (lane == 0) mbar_arrive(cx.afree(kb >> 2)); }
              else if (t1 && kb == 3) bar_arrive(4);
            }
          };
          if (j < 2) gemm8<0, 0>(cx, acc, 16 * j + 8 * w, pre, post);
          else gemm8<1, 0>(cx, acc, 16 * j + 8 * w, pre, post);
          MARK(mode * 1000 + j * 10 + 1); STAMP(2 + 2 * j);
          if (tmaA) ar++;
          const float sc = j < 2 ? 4.f * 0.04419417382415922f * 1.4426950408889634f : 1.f;
          uint32_t pk[64];
#pragma unroll
          for (int i = 0; i < 64; i++) pk[i] = pack2(acc[2 * i] * sc, acc[2 * i + 1] * sc);
          if (t1) {
            if (w == 0) bar_sync(4);
#pragma unroll
            for (int ks = 0; ks < 16; ks++)
              stsm4(sb + OFF_Q + (4 * w + (ks >> 2)) * CH + moff + (((2 * (ks & 3) + mu) ^ mx) << 4), pk[4 * ks], pk[4 * ks + 1], pk[4 * ks + 2], pk[4 * ks + 3]);
            fence_async_smem();
            bar_arrive(w ? 6 : 5);
          } else {
            const int blk = s + 4 * (j < 2 ? j : (j < 6 ? (j >> 2) : (j & 1)));
            uint8_t* dst = (j < 2 ? g_wqk + blk * TILE : g_wf + (j < 6 ? 8 + blk : blk) * TILE) + 4 * w * CH;
            const int r0 = j >= 6 ? sigma(rlo) : rlo, r1 = j >= 6 ? sigma(rlo + 8) : rlo + 8;
            uint8_t* d0 = dst + r0 * 128, * d1 = dst + r1 * 128;
#pragma unroll
            for (int i = 0; i < 8; i++) {
              const int u = 4 * (i & 1) + c;
              *(uint4*)(d0 + (i >> 1) * CH + ((u ^ (r0 & 7)) << 4)) = make_uint4(pk[8 * i], pk[8 * i + 2], pk[8 * i + 4], pk[8 * i + 6]);
              *(uint4*)(d1 + (i >> 1) * CH + ((u ^ (r1 & 7)) << 4)) = make_uint4(pk[8 * i + 1], pk[8 * i + 3], pk[8 * i + 5], pk[8 * i + 7]);
            }
            __syncwarp();
            if (lane == 0) mbar_arrive(cx.sbar(w));
          }
        }
      }
    } else {
      {
#pragma unroll 1
        for (int h = -1; h < 2; h++) {
          const uint32_t r = 4 * max(h, 0) + (lane >> 3), a = sb + OFF_Q + (8 * warp + r) * 128 + (((lane & 7) ^ r) << 4);
          if (h == 0) { mbar_wait(cx.xbar(), 0); STAMP(300); }
          uint32_t v[8][4];
#pragma unroll
          for (int i = 0; i < 8; i++) lds128(a + i * CH, v[i]);
          const float sh = blo(__shfl_sync(~0u, v[0][0], lane & 24));
          float s1 = 0.f, s2 = 0.f, t1 = 0.f, t2 = 0.f;
#pragma unroll
          for (int i = 0; i < 8; i++)
#pragma unroll
            for (int k = 0; k < 4; k++) {
              const float d = blo(v[i][k]) - sh, e = bhi(v[i][k]) - sh;
              s1 += d; s2 = fmaf(d, d, s2); t1 += e; t2 = fmaf(e, e, t2);
            }
          s1 += t1; s2 += t2;
#pragma unroll
          for (int o = 1; o < 8; o <<= 1) { s1 += __shfl_xor_sync(~0u, s1, o); s2 += __shfl_xor_sync(~0u, s2, o); }
          s1 *= (1.f / DD);
          const float rs = 0.5f * rsqrtf(fmaxf(fmaf(-s1, s1, s2 * (1.f / DD)), 0.f) + 1e-5f), mr = -(sh + s1) * rs;
#pragma unroll
          for (int i = 0; i < 8; i++) {
#pragma unroll
            for (int k = 0; k < 4; k++) v[i][k] = pack2(fmaf(blo(v[i][k]), rs, mr), fmaf(bhi(v[i][k]), rs, mr));
            asm volatile("{\n.reg .pred p;\nsetp.ge.s32 p, %5, 0;\n@p st.shared.v4.b32 [%0], {%1, %2, %3, %4};\n}\n"
                         :: "r"(a + i * CH), "r"(v[i][0]), "r"(v[i][1]), "r"(v[i][2]), "r"(v[i][3]), "r"(h) : "memory");
          }
          if (h == 0) STAMP(301);
        }
        STAMP(302);
        fence_async_smem();
      }
      cluster_wait();
      MARK(510); STAMP(1);
      bar_sync_n(3, 288);
      if (mode != 1) {
        MARK(511); STAMP(2);
        uint32_t qf[16];
#pragma unroll 1
        for (int ph = 0; ph < 3; ph++) {
          gemm8<1, N_ATT0 - NS>(cx, acc, 16 * ph + 8 * w, [](int) {}, [&](int kb) { if (ph == 2 && w == 1 && kb == 3) bar_arrive(4); });
          MARK(512 + 2 * ph); STAMP(3 + 2 * ph);
          if (ph < 2) {
            float s1a = 0.f, s2a = 0.f, s1b = 0.f, s2b = 0.f;
            uint8_t* d = g_uc + (size_t)(2 * pairi + rank + (ph ? 0 : 128)) * TILE + 4 * w * CH + rlo * 128;
#pragma unroll
            for (int i = 0; i < 8; i++) {
              uint32_t pa[4], pb[4];
#pragma unroll
              for (int jj = 0; jj < 4; jj++) {
                const int j = 4 * i + jj;
                const float a0 = gelu2(acc[4 * j]), a1 = gelu2(acc[4 * j + 1]), b0 = gelu2(acc[4 * j + 2]), b1 = gelu2(acc[4 * j + 3]);
                acc[4 * j] = a0; acc[4 * j + 1] = a1; acc[4 * j + 2] = b0; acc[4 * j + 3] = b1;
                pa[jj] = pack2(a0, a1); pb[jj] = pack2(b0, b1);
              }
              uint8_t* e = d + (i >> 1) * CH + (((4 * (i & 1) + c) ^ q) << 4);
              STG((uint4*)e, make_uint4(pa[0], pa[1], pa[2], pa[3]));
              STG((uint4*)(e + 1024), make_uint4(pb[0], pb[1], pb[2], pb[3]));
            }
            STAMP(310 + ph);
            if (ph == 0) {
#pragma unroll
              for (int j = 0; j < 32; j++) {
                s1a += acc[4 * j] + acc[4 * j + 1]; s2a = fmaf(acc[4 * j], acc[4 * j], s2a); s2a = fmaf(acc[4 * j + 1], acc[4 * j + 1], s2a);
                s1b += acc[4 * j + 2] + acc[4 * j + 3]; s2b = fmaf(acc[4 * j + 2], acc[4 * j + 2], s2b); s2b = fmaf(acc[4 * j + 3], acc[4 * j + 3], s2b);
              }
#pragma unroll
              for (int o = 1; o < 4; o <<= 1) {
                s1a += __shfl_xor_sync(~0u, s1a, o); s2a += __shfl_xor_sync(~0u, s2a, o);
                s1b += __shfl_xor_sync(~0u, s1b, o); s2b += __shfl_xor_sync(~0u, s2b, o);
              }
              float2* sp = g_st + ((2 * pairi + rank) * 64 + rlo) * 2 + w;
              if (c == 0) { __stcg(sp, make_float2(s1a, s2a)); __stcg(sp + 16, make_float2(s1b, s2b)); }
            }
            __syncwarp();
            if (lane == 0) mbar_arrive(cx.sbar(ph));
          } else {
            mbar_wait(cx.gbar(), 0);
            if (w == 0) bar_sync(4);
#pragma unroll
            for (int i = 0; i < 8; i++) {
              const uint32_t a = sb + OFF_Q + (4 * w + (i >> 1)) * CH + rlo * 128 + (((4 * (i & 1) + c) ^ q) << 4);
              sts128(a, pack2(acc[16 * i], acc[16 * i + 1]), pack2(acc[16 * i + 4], acc[16 * i + 5]), pack2(acc[16 * i + 8], acc[16 * i + 9]), pack2(acc[16 * i + 12], acc[16 * i + 13]));
              sts128(a + 1024, pack2(acc[16 * i + 2], acc[16 * i + 3]), pack2(acc[16 * i + 6], acc[16 * i + 7]), pack2(acc[16 * i + 10], acc[16 * i + 11]), pack2(acc[16 * i + 14], acc[16 * i + 15]));
            }
            fence_async_smem();
            bar_sync_n(12 + w, 128);
          }
          MARK(513 + 2 * ph); STAMP(4 + 2 * ph);
        }
        if (w == 1) {
#pragma unroll
          for (int ks = 0; ks < 4; ks++) ldsm4(sb + OFF_P + moff + (((2 * ks + mu) ^ mx) << 4), qf[4 * ks], qf[4 * ks + 1], qf[4 * ks + 2], qf[4 * ks + 3]);
        }
        bar_arrive(w ? 6 : 5);

        float m0 = -INFINITY, m1 = -INFINITY, l0 = 0.f, l1 = 0.f;
        const uint32_t exa = sb + OFF_EX + (tid & 127) * 16;
        const uint32_t dq = desc_k(sb + OFF_Q), dp = desc_k(sb + OFF_P), dk0 = desc_k(sb), dv = desc_mn(sb), eb = cx.empty(0);
        const uint32_t pw = sb + OFF_P + moff;
        float S[32];
        uint32_t P[16];
        float f0, f1, i0, i1;
        zero_regs(acc);
        auto rescale = [&]() {
#pragma unroll
          for (int j = 0; j < 32; j++) { acc[4 * j] *= f0; acc[4 * j + 1] *= f0; acc[4 * j + 2] *= f1; acc[4 * j + 3] *= f1; }
        };
        auto recv_px = [&](uint32_t sl, bool live, int kmax) {
          bar_sync(2 - w);
          float a, b;
          asm volatile("ld.shared.v4.f32 {%0, %1, %2, %3}, [%4];" : "=f"(a), "=f"(b), "=f"(l0), "=f"(l1) : "r"(exa) : "memory");
          if (__builtin_expect(live && __any_sync(~0u, a != m0 || b != m1), 0)) { f0 = ex2(m0 - a); f1 = ex2(m1 - b); rescale(); }
          m0 = a; m1 = b;
          const uint32_t db = dv + sl * (SLOT >> 4);
          wg_fence();
#pragma unroll
          for (int k = 0; k < 4; k++) if (k < kmax) wgmma_ss_n256_tb1(acc, dp + k * 2, db + k * 128, 1);
        };
        auto qk_lo = [&](uint32_t sl, int k0, int k1) {
          const uint32_t dk = dk0 + sl * (SLOT >> 4);
          wg_fence();
#pragma unroll
          for (int k = 0; k < 16; k++)
            if (k >= k0 && k < k1) wgmma_ss_n64_tb0(S, dq + (k >> 2) * 512 + (k & 3) * 2, dk + (k >> 2) * 512 + (k & 3) * 2, 1);
          wg_commit();
        };
        auto qk_hi = [&](uint32_t sl, int k0, int k1) {
          const uint32_t dk = dk0 + sl * (SLOT >> 4);
          wg_fence();
#pragma unroll
          for (int k = 0; k < 12; k++)
            if (k >= k0 && k < k1) wgmma_ss_n64_tb0(S, dq + 2048 + (k >> 2) * 512 + (k & 3) * 2, dk + (k >> 2) * 512 + (k & 3) * 2, 1);
#pragma unroll
          for (int k = 0; k < 4; k++)
            if (k1 == 16) wgmma_rs_n64_tb0(S, qf[4 * k], qf[4 * k + 1], qf[4 * k + 2], qf[4 * k + 3], dk + 1536 + k * 2, 1);
          wg_commit();
        };
        auto expsum = [&](float d0, float d1, float& s0, float& s1, bool sub, int j0, int j1) {
#pragma unroll
          for (int j = j0; j < j1; j++) {
            float a0 = ex2(sub ? S[4 * j] - d0 : S[4 * j]), a1 = ex2(sub ? S[4 * j + 1] - d0 : S[4 * j + 1]);
            float b0 = ex2(sub ? S[4 * j + 2] - d1 : S[4 * j + 2]), b1 = ex2(sub ? S[4 * j + 3] - d1 : S[4 * j + 3]);
            s0 += a0 + a1; s1 += b0 + b1;
            P[2 * j] = pack2(a0, a1); P[2 * j + 1] = pack2(b0, b1);
          }
        };
        auto softmax = [&]() -> bool {
          float s0 = 0.f, s1 = 0.f;
          expsum(0.f, 0.f, s0, s1, false, 0, 8);
          bool chg = false;
          if (__builtin_expect(__any_sync(~0u, s0 > PMAX || s1 > PMAX || m0 != i0 || m1 != i1), 0)) {
            float x0 = fmaxf(S[0], S[1]), x1 = fmaxf(S[2], S[3]);
#pragma unroll
            for (int j = 1; j < 8; j++) { x0 = fmaxf(x0, fmaxf(S[4 * j], S[4 * j + 1])); x1 = fmaxf(x1, fmaxf(S[4 * j + 2], S[4 * j + 3])); }
            x0 = fmaxf(x0, __shfl_xor_sync(~0u, x0, 1)); x1 = fmaxf(x1, __shfl_xor_sync(~0u, x1, 1));
            x0 = fmaxf(x0, __shfl_xor_sync(~0u, x0, 2)); x1 = fmaxf(x1, __shfl_xor_sync(~0u, x1, 2));
            x0 += i0; x1 += i1;
            chg = __any_sync(~0u, x0 > m0 + 6.f || x1 > m1 + 6.f);
            if (chg) {
              x0 = fmaxf(x0, m0); x1 = fmaxf(x1, m1);
              f0 = ex2(m0 - x0); f1 = ex2(m1 - x1);
              m0 = x0; m1 = x1;
              l0 *= f0; l1 *= f1;
            }
            s0 = 0.f; s1 = 0.f;
            expsum(m0 - i0, m1 - i1, s0, s1, true, 0, 8);
          }
          l0 += s0; l1 += s1;
          return chg;
        };
        auto sinit = [&](bool first) {
          i0 = first ? 0.f : m0; i1 = first ? 0.f : m1;
#pragma unroll
          for (int j = 0; j < 8; j++) { S[4 * j] = -i0; S[4 * j + 1] = -i0; S[4 * j + 2] = -i1; S[4 * j + 3] = -i1; }
          fence_regs(S);
        };
        auto send = [&]() {
#pragma unroll
          for (int ks = 0; ks < 4; ks++) stsm4(pw + (((2 * ks + mu) ^ mx) << 4), P[4 * ks], P[4 * ks + 1], P[4 * ks + 2], P[4 * ks + 3]);
          asm volatile("st.shared.v4.f32 [%0], {%1, %2, %3, %4};" :: "r"(exa), "f"(m0), "f"(m1), "f"(l0), "f"(l1) : "memory");
          fence_async_smem();
          bar_arrive(1 + w);
        };
        auto po = [&](uint32_t sl) {
          const uint32_t db = dv + sl * (SLOT >> 4);
          wg_fence();
#pragma unroll
          for (int k = 0; k < 4; k++) wgmma_rs_n256_tb1(acc, P[4 * k], P[4 * k + 1], P[4 * k + 2], P[4 * k + 3], db + k * 128, 1);
          wg_commit();
        };
        if (w == 1) bar_sync(5);
        uint32_t s0 = (N_ATT0 + 2 * w) % NS, s1 = (N_ATT0 + 2 * w + 1) % NS, sm = (N_ATT0 + 2 * w - 1) % NS;
#pragma unroll 1
        for (int t = w; t < NTILE; t += 2) {
          MARK(600 + t); FSTAMP(32 + (t >> 1) * 8);
          sinit(t < 2);
          const uint32_t e1 = eb + 8 * s1, em = eb + 8 * sm, em2 = em + (MCF || t < NTILE - 2 ? cx.pdelta : 0);
          const uint32_t fb1 = cx.fb + 8 * s1, par1 = (cx.ph >> s1) & 1;
          mbar_wait(cx.fb + 8 * s0, (cx.ph >> s0) & 1);
          cx.ph ^= (1u << s0) | (1u << s1);
          {
            const uint32_t da = dq + w * 2048, dk = dk0 + s0 * (SLOT >> 4);
            wg_fence();
#pragma unroll
            for (int k = 0; k < QKA; k++) wgmma_ss_n64_tb0(S, da + (k >> 2) * 512 + (k & 3) * 2, dk + (k >> 2) * 512 + (k & 3) * 2, 1);
            wg_commit();
          }
          wg_wait<1>();
          fence_regs(acc);
          fence_regs(P);
          arrive2(e1, e1 + cx.pdelta, cx.l0 && t >= 2);
          if (w == 0) qk_lo(s0, QKA, 16); else qk_hi(s0, QKA, 16);
          if (t == 0) {
            bar_sync(6);
#pragma unroll
            for (int ks = 0; ks < 4; ks++) ldsm4(pw + (((2 * ks + mu) ^ mx) << 4), qf[4 * ks], qf[4 * ks + 1], qf[4 * ks + 2], qf[4 * ks + 3]);
          }
          FSTAMP(33 + (t >> 1) * 8);
          mbar_wait(fb1, par1);
          if (w == 0) qk_hi(s1, 0, 16); else qk_lo(s1, 0, 16);
          FSTAMP(34 + (t >> 1) * 8);
          if (t > 0) {
            recv_px(sm, t > 1, 4);
            wg_commit();
            wg_wait<1>();
          } else {
            wg_wait<0>();
          }
          fence_regs(S);
          FSTAMP(35 + (t >> 1) * 8);
          if (t >= NTILE - 2) {
            if (lane == 0) mbar_arrive(cx.afree(0));
            if (t == NTILE - 1) {
#pragma unroll
              for (int i = 16; i < 32; i++) S[i] = -INFINITY;
            }
          }
          const bool chg = softmax();
          FSTAMP(36 + (t >> 1) * 8);
          wg_wait<0>();
          fence_regs(acc);
          FSTAMP(37 + (t >> 1) * 8);
          arrive2(em, em2, cx.l0 && t > 0);
          if (__builtin_expect(chg && t > 0, 0)) rescale();
          po(s0);
          FSTAMP(38 + (t >> 1) * 8);
          send();
          FSTAMP(39 + (t >> 1) * 8);
          s1 = s0; s0 = sm; sm = sm ? sm - 1 : NS - 1;
        }
        wg_wait<0>();
        fence_regs(acc);
        cx.release(N_ATT0 + 2 * (NTILE - 1 - w));
        if (w == 1) {
          const uint32_t n = N_ATT0 + 2 * (NTILE - 1) + 1;
          recv_px(n % NS, true, 4);
          wg_commit();
          wg_wait<0>();
          fence_regs(acc);
          cx.release(n);
          if (lane == 0) mbar_arrive(cx.afree(1));
        }
        STAMP(9);
        l0 += __shfl_xor_sync(~0u, l0, 1); l1 += __shfl_xor_sync(~0u, l1, 1);
        l0 += __shfl_xor_sync(~0u, l0, 2); l1 += __shfl_xor_sync(~0u, l1, 2);
        uint32_t gp[64];
        {
          const float r0 = 2.f * __frcp_rn(l0), r1 = 2.f * __frcp_rn(l1);
#pragma unroll
          for (int j = 0; j < 32; j++) { gp[2 * j] = pack2(acc[4 * j] * r0, acc[4 * j + 1] * r0); gp[2 * j + 1] = pack2(acc[4 * j + 2] * r1, acc[4 * j + 3] * r1); }
        }
        const int La = 64 * (int)rank + rlo, Lb = La + 8;
        const bool va = La >= 1 && La <= 125, vb = Lb <= 125;
        const size_t goff = ((size_t)batch * TT + row0 + rlo) * DD + 256 * w + 8 * c;
        STAMP(10);
        zero_regs(acc);
        uint32_t sl = (N_FIN0 + w) % NS, e = 0, fb = cx.fb + 8 * sl, par = (cx.ph >> sl) & 1, db = dv + sl * (SLOT >> 4);
        auto next = [&](bool rel) {
          const uint32_t pe = e;
          e = eb + 8 * sl;
          cx.ph ^= 1u << sl;
          sl = sl >= NS - 2 ? sl - (NS - 2) : sl + 2;
          fb = cx.fb + 8 * sl; par = (cx.ph >> sl) & 1; db = dv + sl * (SLOT >> 4);
          wg_wait<1>();
          arrive2(pe, pe + (MCF ? cx.pdelta : 0), cx.l0 && rel);
        };
        uint32_t xr[64];
        auto resid = [&](int i0) {
#pragma unroll
          for (int i = i0; i < i0 + 4; i++) {
            const uint4 u = va ? __ldg((const uint4*)(x + goff + 32 * i)) : make_uint4(0, 0, 0, 0);
            const uint4 v = vb ? __ldg((const uint4*)(x + goff + 8 * DD + 32 * i)) : make_uint4(0, 0, 0, 0);
            xr[8 * i] = u.x; xr[8 * i + 1] = u.y; xr[8 * i + 2] = u.z; xr[8 * i + 3] = u.w;
            xr[8 * i + 4] = v.x; xr[8 * i + 5] = v.y; xr[8 * i + 6] = v.z; xr[8 * i + 7] = v.w;
          }
        };
        auto ss = [&](uint32_t da, bool rel) {
          mbar_wait(fb, par);
          wg_fence();
#pragma unroll
          for (int k = 0; k < 4; k++) wgmma_ss_n256_tb1(acc, da + k * 2, db + k * 128, 1);
          wg_commit();
          next(rel);
        };
#pragma unroll 1
        for (int kb = 0; kb < 8; kb++) {
          if (kb == 0 || kb == 7) mbar_wait(cx.afull(kb & 1), 0);
          ss(dq + kb * (CH >> 4), kb > 0);
        }
        STAMP(11);
#pragma unroll
        for (int kb = 0; kb < 4; kb++) {
          mbar_wait(fb, par);
          wg_fence();
#pragma unroll
          for (int k = 0; k < 4; k++) wgmma_rs_n256_tb1(acc, gp[16 * kb + 4 * k], gp[16 * kb + 4 * k + 1], gp[16 * kb + 4 * k + 2], gp[16 * kb + 4 * k + 3], db + k * 128, 1);
          wg_commit();
          next(true);
          if (kb == 0) bar_arrive(7 + w);
          if (kb == 1) {
            bar_sync(8 - w);
#pragma unroll
            for (int ks = 0; ks < 16; ks++)
              stsm4(sb + OFF_Q + (4 * w + (ks >> 2)) * CH + moff + (((2 * (ks & 3) + mu) ^ mx) << 4), gp[4 * ks], gp[4 * ks + 1], gp[4 * ks + 2], gp[4 * ks + 3]);
            fence_async_smem();
            bar_arrive(9 + w);
          }
        }
        STAMP(12);
        bar_sync(10 - w);
        STAMP(13);
        auto half = [&](auto o, uint32_t da, bool last = false) {
          mbar_wait(fb, par);
          wg_fence();
#pragma unroll
          for (int k = 0; k < 8; k++) wgmma_ss_n128_tb1<o.value>(acc, da + (k >> 2) * (CH >> 4) + (k & 3) * 2, db + (k >> 2) * 1024 + (k & 3) * 128, 1);
          wg_commit();
          if (!last) next(true);
        };
        auto fin = [&](int i0, int i1) {
#pragma unroll
          for (int j = 16 * i0; j < 16 * i1; j++) asm volatile("" : "+f"(acc[j]) :: "memory");
#pragma unroll
          for (int i = i0; i < i1; i++) {
            const uint32_t* a = &xr[8 * i];
            const uint32_t* b = &xr[8 * i + 4];
            uint4 oa, ob;
            oa.x = pack2(acc[16 * i] + blo(a[0]), acc[16 * i + 1] + bhi(a[0])); oa.y = pack2(acc[16 * i + 4] + blo(a[1]), acc[16 * i + 5] + bhi(a[1]));
            oa.z = pack2(acc[16 * i + 8] + blo(a[2]), acc[16 * i + 9] + bhi(a[2])); oa.w = pack2(acc[16 * i + 12] + blo(a[3]), acc[16 * i + 13] + bhi(a[3]));
            ob.x = pack2(acc[16 * i + 2] + blo(b[0]), acc[16 * i + 3] + bhi(b[0])); ob.y = pack2(acc[16 * i + 6] + blo(b[1]), acc[16 * i + 7] + bhi(b[1]));
            ob.z = pack2(acc[16 * i + 10] + blo(b[2]), acc[16 * i + 11] + bhi(b[2])); ob.w = pack2(acc[16 * i + 14] + blo(b[3]), acc[16 * i + 15] + bhi(b[3]));
            if (va) STO((uint4*)(out + goff + 32 * i), oa);
            if (vb) STO((uint4*)(out + goff + 8 * DD + 32 * i), ob);
          }
        };
        const uint32_t dpa = dq + 4 * (1 - w) * (CH >> 4);
        wg_wait<0>();
        fence_regs(gp);
#pragma unroll
        for (int j = 0; j < 128; j++) { float t; asm volatile("mov.b32 %0, %1;" : "=f"(t) : "f"(acc[j]) : "memory"); acc[j] = t; }
        half(IC<0>(), dpa);
        resid(0);
        half(IC<0>(), dpa + 2 * (CH >> 4));
        resid(4);
        half(IC<64>(), dpa);
        fin(0, TSPLIT);
        half(IC<64>(), dpa + 2 * (CH >> 4), true);
        fin(TSPLIT, 4);
        wg_wait<0>();
        STAMP(14);
        fin(4, 8);
      }
    }
    MARK(mode * 1000 + 999); STAMP(20); GSTAMP(501);
    if (lane == 0) mbar_arrive(cx.dbar());
    if (tid == 0 && mode != 1) atomicAdd(&g_flags[F_DONE * 32], 1u);
    __syncwarp();
    cluster_arrive();
    cluster_wait();
  }
}

typedef CUresult (*EncodeFn)(CUtensorMap*, CUtensorMapDataType, cuuint32_t, void*, const cuuint64_t*, const cuuint64_t*, const cuuint32_t*,
                             const cuuint32_t*, CUtensorMapInterleave, CUtensorMapSwizzle, CUtensorMapL2promotion, CUtensorMapFloatOOBfill);

static void make_map(EncodeFn fn, CUtensorMap* m, void* p, int rows, int cols, int box_rows, int box_blks) {
  cuuint64_t dims[3] = {64, (cuuint64_t)rows, (cuuint64_t)(cols / 64)};
  cuuint64_t strides[2] = {(cuuint64_t)cols * 2, 128};
  cuuint32_t box[3] = {64, (cuuint32_t)box_rows, (cuuint32_t)box_blks};
  cuuint32_t es[3] = {1, 1, 1};
  fn(m, CU_TENSOR_MAP_DATA_TYPE_BFLOAT16, 3, p, dims, strides, box, es, CU_TENSOR_MAP_INTERLEAVE_NONE, CU_TENSOR_MAP_SWIZZLE_128B,
     CU_TENSOR_MAP_L2_PROMOTION_L2_256B, CU_TENSOR_MAP_FLOAT_OOB_FILL_NONE);
}

static void make_map4(EncodeFn fn, CUtensorMap* m, void* p, int rows, int brows, int box_blks) {
  cuuint64_t dims[4] = {64, (cuuint64_t)rows, 8, 2};
  cuuint64_t strides[3] = {DD * 2, 128, (cuuint64_t)brows * DD * 2};
  cuuint32_t box[4] = {64, 64, (cuuint32_t)box_blks, 1};
  cuuint32_t es[4] = {1, 1, 1, 1};
  fn(m, CU_TENSOR_MAP_DATA_TYPE_BFLOAT16, 4, p, dims, strides, box, es, CU_TENSOR_MAP_INTERLEAVE_NONE, CU_TENSOR_MAP_SWIZZLE_128B,
     CU_TENSOR_MAP_L2_PROMOTION_L2_256B, CU_TENSOR_MAP_FLOAT_OOB_FILL_NONE);
}

}

extern "C" void kernel_launch(void* const* d_in, const int* in_sizes, int n_in, void* d_out, int out_size) {
  using namespace bf;
  static EncodeFn fn = nullptr;
  static int fused = 0;
  static void* xa_ptr = nullptr;
  if (!fn) {
    void* p = nullptr;
    cudaDriverEntryPointQueryResult qr;
    cudaGetDriverEntryPoint("cuTensorMapEncodeTiled", &p, cudaEnableDefault, &qr);
    fn = (EncodeFn)p;
    cudaGetSymbolAddress(&xa_ptr, g_xa);
    cudaFuncSetAttribute(bf_kernel, cudaFuncAttributeMaxDynamicSharedMemorySize, SMEM_BYTES);
    cudaLaunchConfig_t cfg = {};
    cfg.gridDim = dim3(NCTA); cfg.blockDim = dim3(384); cfg.dynamicSmemBytes = SMEM_BYTES;
    cudaLaunchAttribute at[1];
    at[0].id = cudaLaunchAttributeClusterDimension; at[0].val.clusterDim.x = 2; at[0].val.clusterDim.y = 1; at[0].val.clusterDim.z = 1;
    cfg.attrs = at; cfg.numAttrs = 1;
    int nc = 0;
    cudaOccupancyMaxActiveClusters(&nc, bf_kernel, &cfg);
    fused = nc >= NCTA / 2;
  }
  Maps maps;
  make_map(fn, &maps.q, d_in[1], 512, 512, 64, 2);
  make_map(fn, &maps.k, d_in[2], 512, 512, 128, 1);
  make_map(fn, &maps.v, d_in[3], 512, 512, 64, 2);
  make_map(fn, &maps.ao, d_in[4], 512, 512, 64, 2);
  make_map(fn, &maps.up, d_in[5], 512, 1024, 64, 2);
  make_map(fn, &maps.dn, d_in[7], 512, 512, 64, 2);
  make_map(fn, &maps.mg, d_in[8], 1024, 512, 64, 2);
  make_map4(fn, &maps.x, d_in[0], TT, TT, 4);
  make_map4(fn, &maps.xs, xa_ptr, TT + 1, TT + 1, 1);
  make_map4(fn, &maps.xl, (uint8_t*)xa_ptr + DD * 2, TT, TT + 1, 2);
  Ptrs wp = {(const uint8_t*)d_in[1], (const uint8_t*)d_in[2], (const uint8_t*)d_in[3], (const uint8_t*)d_in[4],
             (const uint8_t*)d_in[5], (const uint8_t*)d_in[7], (const uint8_t*)d_in[8]};
  const __nv_bfloat16* x = (const __nv_bfloat16*)d_in[0];
  const __nv_bfloat16* dw = (const __nv_bfloat16*)d_in[6];
  __nv_bfloat16* out = (__nv_bfloat16*)d_out;
  if (fused) {
    bf_kernel<<<NCTA, 384, SMEM_BYTES>>>(maps, wp, x, dw, out, 0);
  } else {
    bf_kernel<<<NCTA, 384, SMEM_BYTES>>>(maps, wp, x, dw, out, 1);
    bf_kernel<<<NCTA, 384, SMEM_BYTES>>>(maps, wp, x, dw, out, 2);
  }
}
```
